```python
import torch

def _softmax(x, axis=-1):
    return torch.softmax(x, dim=axis)
def _gelu(x):
    return torch.nn.functional.gelu(x, approximate="tanh")
def _silu(x):
    return torch.nn.functional.silu(x)
def _sigmoid(x):
    return torch.sigmoid(x)
def _layernorm(x, axis=-1, eps=1e-5):
    m = x.mean(dim=axis, keepdim=True)
    v = x.var(dim=axis, keepdim=True, unbiased=False)
    return (x - m) / torch.sqrt(v + eps)
def _scatter_add(tgt, idx, src, axis=0):
    return tgt.clone().index_add_(axis, idx, src)
def _segment_sum(src, seg, n):
    out = torch.zeros((n,) + src.shape[1:], dtype=src.dtype)
    return out.index_add_(0, seg, src)
def _pad(x, pw):
    flat = tuple(v for pair in reversed(pw) for v in pair)
    return torch.nn.functional.pad(x, flat)

kernel_name = 'parallel_sum__sliding_local_dilated__glu_gated_glu__prompt'

def setup_inputs():

    _w = (lambda a: (lambda t: t.to(torch.bfloat16) if t.is_floating_point() else t)(torch.as_tensor(a)))
    def _A_setup():
        B, S, D = 1, 2048, 576
        return {
            "x": _w((lambda *s: torch.randn(*s, dtype=torch.bfloat16) * 0.05)(B, S, D)),
            "wqkv": _w((lambda *s: torch.randn(*s, dtype=torch.bfloat16) * 0.05)(D, 3 * D)),
            "wo": _w((lambda *s: torch.randn(*s, dtype=torch.bfloat16) * 0.05)(D, D)),
        }
    _A_in = _A_setup()

    def _B_setup():
        B, S, D, F = 1, 2048, 576, 4608
        return {
            "x": _w((lambda *s: torch.randn(*s, dtype=torch.bfloat16) * 0.05)(B, S, D)),
            "w_gate": _w((lambda *s: torch.randn(*s, dtype=torch.bfloat16) * 0.05)(D, F)),
            "w_up": _w((lambda *s: torch.randn(*s, dtype=torch.bfloat16) * 0.05)(D, F)),
            "w_down": _w((lambda *s: torch.randn(*s, dtype=torch.bfloat16) * 0.05)(F, D)),
        }
    _B_in = _B_setup()

    return {
        "A_x": _A_in["x"],
        "A_wqkv": _A_in["wqkv"],
        "A_wo": _A_in["wo"],
        "B_x": _B_in["x"],
        "B_w_gate": _B_in["w_gate"],
        "B_w_up": _B_in["w_up"],
        "B_w_down": _B_in["w_down"],
    }

def reference(A_x, A_wqkv, A_wo, B_x, B_w_gate, B_w_up, B_w_down):
    def _A_ref(x, wqkv, wo):
        B, S, D = x.shape
        H = 32; Dh = D // H
        W, dil = 8, 2
        qkv = (lambda x, *d: x.permute(*d))((x @ wqkv).reshape(B, S, 3, H, Dh), 2, 0, 3, 1, 4)
        q, k, v = qkv[0], qkv[1], qkv[2]
        scale = Dh ** -0.5
        pos = torch.arange(S)
        off = torch.arange(W) * dil
        idx = pos[:, None] - off[None, :]
        mask = idx >= 0
        idx_c = torch.where(mask, idx, 0).reshape(-1)
        kg = k[:, :, idx_c, :].reshape(B, H, S, W, Dh)
        vg = v[:, :, idx_c, :].reshape(B, H, S, W, Dh)
        logits = torch.einsum("bhsd,bhswd->bhsw", q, kg) * scale
        logits = torch.where(mask[None, None, :, :], logits, -1e9)
        attn = _softmax(logits, axis=-1)
        o = torch.einsum("bhsw,bhswd->bhsd", attn, vg)
        return (lambda x, *d: x.permute(*d))(o, 0, 2, 1, 3).reshape(B, S, D) @ wo

    def _B_ref(x, w_gate, w_up, w_down):
        g = torch.einsum("bsd,df->bsf", x, w_gate)
        u = torch.einsum("bsd,df->bsf", x, w_up)
        h = _sigmoid(g) * u
        return torch.einsum("bsf,fd->bsd", h, w_down)

    x = A_x
    xn = _layernorm(x, axis=-1)
    return x + _A_ref(xn, A_wqkv, A_wo) + _B_ref(xn, B_w_gate, B_w_up, B_w_down)
```

```cpp
#include <cuda_runtime.h>
#include <cuda.h>
#include <cuda_bf16.h>
#include <stdint.h>

namespace {

constexpr int SEQ = 2048, DM = 576, FF = 4608;
constexpr int NSLOT = 9;
constexpr int SLOT = 8192;
constexpr int HS = 16384;
constexpr int OFF_RING = 9 * HS;
constexpr int OFF_WOR = OFF_RING + NSLOT * SLOT;
constexpr int OFF_BAR = OFF_WOR + 9 * 1024;
constexpr int SMEM_BYTES = OFF_BAR + 512;
constexpr int OFF_W24 = 4 * HS;
constexpr int OTILE = 128 * 144;
constexpr int OFF_ATT = 6 * HS;
constexpr int AV = 5504, AQ = 11008;
constexpr int BAR_FULL = 0, BAR_EMPTY = 9, BAR_X = 18, BAR_WOR = 36, BAR_XDONE = 37, BAR_W24 = 38, BAR_QST = 39, BAR_QFREE = 43,
              BAR_ATI = 44, BAR_ATD = 46, BAR_O = 48, BAR_OFREE = 49;
#define NXB 9
#define PUNROLL 1
constexpr int kPUnroll = PUNROLL;
constexpr int SPIN_LIMIT = 1 << 22;

__device__ uint4 g_qkv[216 * SEQ];
__device__ uint32_t g_o[128 * 128 * 36];
__device__ unsigned g_cnt[16 * 32];
__device__ unsigned g_done;
__device__ unsigned g_epoch;
#define TR(i)
#define TRG(i)
#define TRC(i)

__device__ __forceinline__ uint32_t smem_u32(const void* p) { return (uint32_t)__cvta_generic_to_shared(p); }
__device__ __forceinline__ void wg_fence() { asm volatile("wgmma.fence.sync.aligned;\n" ::: "memory"); }
__device__ __forceinline__ void wg_commit() { asm volatile("wgmma.commit_group.sync.aligned;\n" ::: "memory"); }
template <int N> __device__ __forceinline__ void wg_wait() { asm volatile("wgmma.wait_group.sync.aligned %0;\n" ::"n"(N) : "memory"); }
__device__ __forceinline__ void mbar_init(uint32_t a, int c) { asm volatile("mbarrier.init.shared::cta.b64 [%0], %1;" ::"r"(a), "r"(c) : "memory"); }
__device__ __forceinline__ void mbar_expect(uint32_t a, uint32_t b) { asm volatile("mbarrier.arrive.expect_tx.shared::cta.b64 _, [%0], %1;" ::"r"(a), "r"(b) : "memory"); }
__device__ __forceinline__ void mbar_arrive(uint32_t a) { asm volatile("mbarrier.arrive.shared::cta.b64 _, [%0];" ::"r"(a) : "memory"); }
__device__ __forceinline__ void mbar_wait(uint32_t a, uint32_t par) {
  uint32_t ok; int it = 0;
  while (true) {
    asm volatile("{\n.reg .pred p;\nmbarrier.try_wait.parity.shared::cta.b64 p, [%1], %2;\nselp.u32 %0,1,0,p;\n}\n" : "=r"(ok) : "r"(a), "r"(par) : "memory");
    if (ok) break;
    if (++it > SPIN_LIMIT) __trap();
  }
}
__device__ __forceinline__ uint32_t mbar_try(uint32_t a, uint32_t par) {
  uint32_t ok;
  asm volatile("{\n.reg .pred p;\nmbarrier.try_wait.parity.shared::cta.b64 p, [%1], %2;\nselp.u32 %0,1,0,p;\n}\n" : "=r"(ok) : "r"(a), "r"(par) : "memory");
  return ok;
}
__device__ __forceinline__ void fence_mbar_init() { asm volatile("fence.mbarrier_init.release.cluster;" ::: "memory"); }
__device__ __forceinline__ void fence_async_smem() { asm volatile("fence.proxy.async.shared::cta;\n" ::: "memory"); }
__device__ __forceinline__ void fence_async_gmem() { asm volatile("fence.proxy.async.global;\n" ::: "memory"); }
__device__ __forceinline__ void tma2d(uint32_t dst, const CUtensorMap* m, int c0, int c1, uint32_t bar) {
  asm volatile("cp.async.bulk.tensor.2d.shared::cluster.global.mbarrier::complete_tx::bytes [%0], [%1, {%3, %4}], [%2];" ::"r"(dst), "l"(m), "r"(bar), "r"(c0), "r"(c1) : "memory");
}
__device__ __forceinline__ void bulk_g2s(uint32_t dst, const void* src, uint32_t bytes, uint32_t bar) {
  asm volatile("cp.async.bulk.shared::cluster.global.mbarrier::complete_tx::bytes [%0], [%1], %2, [%3];" ::"r"(dst), "l"(src), "r"(bytes), "r"(bar) : "memory");
}
__device__ __forceinline__ void tma2d_store(const CUtensorMap* m, uint32_t src, int c0, int c1) {
  asm volatile("cp.async.bulk.tensor.2d.global.shared::cta.tile.bulk_group [%0, {%2, %3}], [%1];" ::"l"(m), "r"(src), "r"(c0), "r"(c1) : "memory");
}
__device__ __forceinline__ bool elect() {
  uint32_t p;
  asm volatile("{\n.reg .pred p;\nelect.sync _|p, 0xffffffff;\nselp.u32 %0, 1, 0, p;\n}\n" : "=r"(p));
  return p;
}
__device__ __forceinline__ void tma2d_red(const CUtensorMap* m, uint32_t src, int c0, int c1) {
  asm volatile("cp.reduce.async.bulk.tensor.2d.global.shared::cta.add.tile.bulk_group [%0, {%2, %3}], [%1];" ::"l"(m), "r"(src), "r"(c0), "r"(c1) : "memory");
}
__device__ __forceinline__ void bulk_commit() { asm volatile("cp.async.bulk.commit_group;" ::: "memory"); }
__device__ __forceinline__ void bulk_wait_all() { asm volatile("cp.async.bulk.wait_group 0;" ::: "memory"); }
__device__ __forceinline__ void bulk_wait_read_all() { asm volatile("cp.async.bulk.wait_group.read 0;" ::: "memory"); }
__device__ __forceinline__ void ldsm4(uint32_t addr, uint32_t& r0, uint32_t& r1, uint32_t& r2, uint32_t& r3) {
  asm volatile("ldmatrix.sync.aligned.m8n8.x4.shared.b16 {%0,%1,%2,%3}, [%4];" : "=r"(r0), "=r"(r1), "=r"(r2), "=r"(r3) : "r"(addr) : "memory");
}
__device__ __forceinline__ void ldsm2(uint32_t addr, uint32_t& r0, uint32_t& r1) {
  asm volatile("ldmatrix.sync.aligned.m8n8.x2.shared.b16 {%0,%1}, [%2];" : "=r"(r0), "=r"(r1) : "r"(addr) : "memory");
}
__device__ __forceinline__ void stsm4(uint32_t addr, uint32_t r0, uint32_t r1, uint32_t r2, uint32_t r3) {
  asm volatile("stmatrix.sync.aligned.m8n8.x4.shared.b16 [%0], {%1,%2,%3,%4};" ::"r"(addr), "r"(r0), "r"(r1), "r"(r2), "r"(r3) : "memory");
}
__device__ __forceinline__ void stsm2(uint32_t addr, uint32_t r0, uint32_t r1) {
  asm volatile("stmatrix.sync.aligned.m8n8.x2.shared.b16 [%0], {%1,%2};" ::"r"(addr), "r"(r0), "r"(r1) : "memory");
}
__device__ __forceinline__ void bulk_prefetch(const void* p, uint32_t bytes) { asm volatile("cp.async.bulk.prefetch.L2.global [%0], %1;" ::"l"(p), "r"(bytes) : "memory"); }
template <int N> __device__ __forceinline__ void lds(uint32_t addr, uint32_t* v) {
  if (N == 4) asm volatile("ld.shared.v4.b32 {%0,%1,%2,%3}, [%4];" : "=r"(v[0]), "=r"(v[1]), "=r"(v[2]), "=r"(v[3]) : "r"(addr));
  else if (N == 2) asm volatile("ld.shared.v2.b32 {%0,%1}, [%2];" : "=r"(v[0]), "=r"(v[1]) : "r"(addr));
  else asm volatile("ld.shared.b32 %0, [%1];" : "=r"(v[0]) : "r"(addr));
}
__device__ __forceinline__ uint32_t pack2(float lo, float hi) { uint32_t r; asm("cvt.rn.bf16x2.f32 %0, %1, %2;" : "=r"(r) : "f"(hi), "f"(lo)); return r; }
__device__ __forceinline__ float bf_lo(uint32_t v) { return __uint_as_float(v << 16); }
__device__ __forceinline__ float bf_hi(uint32_t v) { return __uint_as_float(v & 0xffff0000u); }
__device__ __forceinline__ uint32_t bsub2(uint32_t a, uint32_t b) { uint32_t r; asm("sub.rn.bf16x2 %0, %1, %2;" : "=r"(r) : "r"(a), "r"(b)); return r; }
__device__ __forceinline__ float tanh_hw(float x) { float y; asm("tanh.approx.f32 %0, %1;" : "=f"(y) : "f"(x)); return y; }
__device__ __forceinline__ float ex2(float x) { float y; asm("ex2.approx.ftz.f32 %0, %1;" : "=f"(y) : "f"(x)); return y; }
__device__ __forceinline__ unsigned ld_acquire(const unsigned* p) { unsigned v; asm volatile("ld.acquire.gpu.global.u32 %0, [%1];" : "=r"(v) : "l"(p) : "memory"); return v; }
__device__ __forceinline__ void red_release(unsigned* p, unsigned v) { asm volatile("red.release.gpu.global.add.u32 [%0], %1;" ::"l"(p), "r"(v) : "memory"); }
__device__ __forceinline__ void wait_counter(const unsigned* p, unsigned target) {
  int it = 0;
  while ((int)(ld_acquire(p) - target) < 0) { __nanosleep(32); if (++it > SPIN_LIMIT) __trap(); }
}
__device__ __forceinline__ void mma16816(float (&d)[4], uint32_t a0, uint32_t a1, uint32_t a2, uint32_t a3, uint32_t b0, uint32_t b1) {
  asm volatile("mma.sync.aligned.m16n8k16.row.col.f32.bf16.bf16.f32 {%0,%1,%2,%3}, {%4,%5,%6,%7}, {%8,%9}, {%0,%1,%2,%3};"
      : "+f"(d[0]), "+f"(d[1]), "+f"(d[2]), "+f"(d[3]) : "r"(a0), "r"(a1), "r"(a2), "r"(a3), "r"(b0), "r"(b1));
}

__device__ __forceinline__ void mma1688(float (&d)[4], uint32_t a0, uint32_t a1, uint32_t b0) {
  asm volatile("mma.sync.aligned.m16n8k8.row.col.f32.bf16.bf16.f32 {%0,%1,%2,%3}, {%4,%5}, {%6}, {%0,%1,%2,%3};"
               : "+f"(d[0]), "+f"(d[1]), "+f"(d[2]), "+f"(d[3]) : "r"(a0), "r"(a1), "r"(b0));
}

__device__ __forceinline__ void wgmma_rs_n64(float (&d)[32], uint32_t a0, uint32_t a1, uint32_t a2, uint32_t a3, uint64_t db, int sd) {
  asm volatile("{\n.reg .pred p;\nsetp.ne.b32 p, %37, 0;\n"
    "wgmma.mma_async.sync.aligned.m64n64k16.f32.bf16.bf16 {%0, %1, %2, %3, %4, %5, %6, %7, %8, %9, %10, %11, %12, %13, %14, %15, %16, %17, %18, %19, %20, %21, %22, %23, %24, %25, %26, %27, %28, %29, %30, %31}, {%32, %33, %34, %35}, %36, p, 1, 1, 1;\n"
    "}\n"
    : "+f"(d[0]), "+f"(d[1]), "+f"(d[2]), "+f"(d[3]), "+f"(d[4]), "+f"(d[5]), "+f"(d[6]), "+f"(d[7]), "+f"(d[8]), "+f"(d[9]), "+f"(d[10]), "+f"(d[11]), "+f"(d[12]), "+f"(d[13]), "+f"(d[14]), "+f"(d[15]), "+f"(d[16]), "+f"(d[17]), "+f"(d[18]), "+f"(d[19]), "+f"(d[20]), "+f"(d[21]), "+f"(d[22]), "+f"(d[23]), "+f"(d[24]), "+f"(d[25]), "+f"(d[26]), "+f"(d[27]), "+f"(d[28]), "+f"(d[29]), "+f"(d[30]), "+f"(d[31])
    : "r"(a0), "r"(a1), "r"(a2), "r"(a3), "l"(db), "r"(sd));
}

__device__ __forceinline__ void wgmma_ss_n64(float (&d)[32], uint64_t da, uint64_t db, int sd) {
  asm volatile("{\n.reg .pred p;\nsetp.ne.b32 p, %34, 0;\n"
    "wgmma.mma_async.sync.aligned.m64n64k16.f32.bf16.bf16 {%0, %1, %2, %3, %4, %5, %6, %7, %8, %9, %10, %11, %12, %13, %14, %15, %16, %17, %18, %19, %20, %21, %22, %23, %24, %25, %26, %27, %28, %29, %30, %31}, %32, %33, p, 1, 1, 0, 1;\n"
    "}\n"
    : "+f"(d[0]), "+f"(d[1]), "+f"(d[2]), "+f"(d[3]), "+f"(d[4]), "+f"(d[5]), "+f"(d[6]), "+f"(d[7]), "+f"(d[8]), "+f"(d[9]), "+f"(d[10]), "+f"(d[11]), "+f"(d[12]), "+f"(d[13]), "+f"(d[14]), "+f"(d[15]), "+f"(d[16]), "+f"(d[17]), "+f"(d[18]), "+f"(d[19]), "+f"(d[20]), "+f"(d[21]), "+f"(d[22]), "+f"(d[23]), "+f"(d[24]), "+f"(d[25]), "+f"(d[26]), "+f"(d[27]), "+f"(d[28]), "+f"(d[29]), "+f"(d[30]), "+f"(d[31])
    : "l"(da), "l"(db), "r"(sd));
}

__device__ __forceinline__ void wgmma_rs_n24(float (&d)[32], uint32_t a0, uint32_t a1, uint32_t a2, uint32_t a3, uint64_t db, int sd) {
  asm volatile("{\n.reg .pred p;\nsetp.ne.b32 p, %17, 0;\n"
    "wgmma.mma_async.sync.aligned.m64n24k16.f32.bf16.bf16 {%0, %1, %2, %3, %4, %5, %6, %7, %8, %9, %10, %11}, {%12, %13, %14, %15}, %16, p, 1, 1, 1;\n"
    "}\n"
    : "+f"(d[0]), "+f"(d[1]), "+f"(d[2]), "+f"(d[3]), "+f"(d[4]), "+f"(d[5]), "+f"(d[6]), "+f"(d[7]), "+f"(d[8]), "+f"(d[9]), "+f"(d[10]), "+f"(d[11])
    : "r"(a0), "r"(a1), "r"(a2), "r"(a3), "l"(db), "r"(sd));
}

__device__ __forceinline__ void wgmma_ss_n24(float (&d)[32], uint64_t da, uint64_t db, int sd) {
  asm volatile("{\n.reg .pred p;\nsetp.ne.b32 p, %14, 0;\n"
    "wgmma.mma_async.sync.aligned.m64n24k16.f32.bf16.bf16 {%0, %1, %2, %3, %4, %5, %6, %7, %8, %9, %10, %11}, %12, %13, p, 1, 1, 0, 1;\n"
    "}\n"
    : "+f"(d[0]), "+f"(d[1]), "+f"(d[2]), "+f"(d[3]), "+f"(d[4]), "+f"(d[5]), "+f"(d[6]), "+f"(d[7]), "+f"(d[8]), "+f"(d[9]), "+f"(d[10]), "+f"(d[11])
    : "l"(da), "l"(db), "r"(sd));
}

__device__ __forceinline__ uint64_t mkd(uint32_t lo) { return ((uint64_t)0x40000040u << 32) | (uint64_t)lo; }
__device__ __forceinline__ uint64_t mkd_sbo0(uint32_t lo) { return ((uint64_t)0x40000000u << 32) | (uint64_t)lo; }
__device__ __forceinline__ uint64_t mkd24(uint32_t lo) { return ((uint64_t)(9216 >> 4) << 32) | (uint64_t)lo; }

constexpr uint32_t sb = 1024;
constexpr uint32_t bars = sb + OFF_BAR;
constexpr uint32_t RING_LO = ((sb + OFF_RING) >> 4) | (512u << 16);

__device__ __forceinline__ void acc_fence(float (&d)[32]) {
  asm volatile("" : "+f"(d[0]), "+f"(d[1]), "+f"(d[2]), "+f"(d[3]), "+f"(d[4]), "+f"(d[5]), "+f"(d[6]), "+f"(d[7]), "+f"(d[8]), "+f"(d[9]), "+f"(d[10]), "+f"(d[11]), "+f"(d[12]), "+f"(d[13]), "+f"(d[14]), "+f"(d[15]), "+f"(d[16]), "+f"(d[17]), "+f"(d[18]), "+f"(d[19]), "+f"(d[20]), "+f"(d[21]), "+f"(d[22]), "+f"(d[23]), "+f"(d[24]), "+f"(d[25]), "+f"(d[26]), "+f"(d[27]), "+f"(d[28]), "+f"(d[29]), "+f"(d[30]), "+f"(d[31]) :: "memory");
}

template <int V> struct IC { static constexpr int value = V; };

struct Ring {
  int st, prev;
  uint32_t ph;
};

template <int NST, int ID, class M, class F>
__device__ __forceinline__ void run_pass(Ring& R, bool last, float (&other)[32], M&& mma, F&& slice) {
#pragma unroll
  for (int s = 0; s < NST; s++) {
    const uint32_t blo = RING_LO + R.st * (SLOT >> 4);
    wg_fence();
    mma(s, blo);
    wg_commit();
    const int cur = R.st;
    R.st++;
    if (R.st == NSLOT) { R.st = 0; R.ph ^= 1; }
    if (!(last && s == NST - 1)) mbar_wait(bars + (BAR_FULL + R.st) * 8, R.ph);
    slice(s);
    wg_wait<1>();
    if (s == 0) acc_fence(other);
    if (R.prev >= 0 && (threadIdx.x & 127) == 0) mbar_arrive(bars + (BAR_EMPTY + R.prev) * 8);
    R.prev = cur;
  }
}

struct Maps {
  CUtensorMap x, wqkv, wg, wu, wd, woa, wob, out, qs8, qs3, lkv, lq;
};

__global__ void __launch_bounds__(384, 1)
fused_kernel(const __grid_constant__ Maps mp, const uint4* __restrict__ xg, const void* __restrict__ wqkv, uint4* __restrict__ outg) {
  extern __shared__ __align__(1024) uint8_t smem[];
  const int j = blockIdx.x & 7, m = blockIdx.x >> 3;
  const int m0 = m * 128;
  const int warp = __shfl_sync(0xffffffffu, threadIdx.x >> 5, 0), lane = threadIdx.x & 31;

  if (warp == 8) {
    if (elect()) {
      for (int i = 0; i < NXB; i++) mbar_init(bars + (BAR_X + i) * 8, 1);
      fence_mbar_init();
#pragma unroll
      for (int i = 0; i < NXB; i++) {
        const uint32_t b = bars + (BAR_X + i) * 8;
        mbar_expect(b, 147456 / NXB);
        tma2d(sb + (i % 9) * HS + (i / 9) * 8192, &mp.x, (i % 9) * 64, m0 + (i / 9) * 64, b);
      }
    }
  } else if (lane == 0) {
    if (warp == 9) {
      if (smem_u32(smem) != sb) __trap();
      for (int i = 0; i < NSLOT; i++) { mbar_init(bars + (BAR_FULL + i) * 8, 1); mbar_init(bars + (BAR_EMPTY + i) * 8, 2); }
      fence_mbar_init();
    } else if (warp == 10) {
      mbar_init(bars + BAR_WOR * 8, 1);
      mbar_init(bars + BAR_XDONE * 8, 8);
      mbar_init(bars + BAR_W24 * 8, 3);
      for (int i = 0; i < 4; i++) mbar_init(bars + (BAR_QST + i) * 8, 8);
      mbar_init(bars + BAR_QFREE * 8, 1);
      for (int i = 0; i < 2; i++) { mbar_init(bars + (BAR_ATI + i) * 8, 1); mbar_init(bars + (BAR_ATD + i) * 8, 1); }
      mbar_init(bars + BAR_O * 8, 1);
      mbar_init(bars + BAR_OFREE * 8, 8);
      fence_mbar_init();
    } else if (warp == 11) {
      const CUtensorMap* mm = &mp.wqkv;
      for (int i = 0; i < 11; i++) asm volatile("prefetch.tensormap [%0];" ::"l"(mm + i) : "memory");
    }
  }
  __syncthreads();

  if (warp < 8) {
    asm volatile("setmaxnreg.inc.sync.aligned.u32 232;\n");
    const int wg = warp >> 2;
    const int lrow = (warp & 3) * 16 + (lane & 15);
    const uint32_t rowa = sb + wg * 8192 + lrow * 128;
    const uint32_t swz = ((lane >> 4) ^ (lrow & 7)) << 4;
    uint32_t a[128];
    uint32_t sg[18];
    float accA[32], accB[32];
    float rs0, rs1;

    Ring R;
    R.st = 0; R.prev = -1; R.ph = 0;
    uint32_t mp0, mp1;
    {
      float cs[2][4] = {}, c1[2][4] = {}, c2[2][4] = {};
#pragma unroll
      for (int kb = 0; kb <= 9; kb++) {
        if (kb < 9) {
          mbar_wait(bars + (BAR_X + (NXB == 18 ? wg * 9 : 0) + kb) * 8, 0);
          if (kb == 0) TR(40);
          if (kb == 8) TR(41);
#pragma unroll
          for (int kk = 0; kk < 4; kk++) {
            uint32_t* r = (kb < 8) ? &a[kb * 16 + kk * 4] : &sg[kk * 4];
            ldsm4(rowa + kb * HS + (swz ^ (kk << 5)), r[0], r[1], r[2], r[3]);
          }
        }
        if (kb > 0) {
#pragma unroll
          for (int kk = 0; kk < 4; kk++) {
            const uint32_t* r = (kb < 9) ? &a[(kb - 1) * 16 + kk * 4] : &sg[kk * 4];
            mma16816(cs[kk & 1], r[0], r[1], r[2], r[3], 0x3f803f80u, 0x3f803f80u);
            mma1688(c1[0], r[0], r[1], r[0]);
            mma1688(c2[0], r[0], r[1], r[1]);
            mma1688(c1[1], r[2], r[3], r[2]);
            mma1688(c2[1], r[2], r[3], r[3]);
          }
        }
      }
      __syncwarp();
      if (lane == 0) mbar_arrive(bars + BAR_XDONE * 8);
      const float mu0 = (cs[0][0] + cs[1][0]) * (1.f / DM), mu1 = (cs[0][2] + cs[1][2]) * (1.f / DM);
      mp0 = pack2(mu0, mu0); mp1 = pack2(mu1, mu1);
      const int src = (lane & ~3) | (lane >> 3);
      const float q0 = __shfl_sync(0xffffffffu, (lane & 4) ? c1[0][1] + c1[1][1] : c1[0][0] + c1[1][0], src);
      const float q1 = __shfl_sync(0xffffffffu, (lane & 4) ? c2[0][3] + c2[1][3] : c2[0][2] + c2[1][2], src);
      rs0 = rsqrtf(fmaxf(q0 * (1.f / DM) - mu0 * mu0, 0.f) + 1e-5f);
      rs1 = rsqrtf(fmaxf(q1 * (1.f / DM) - mu1 * mu1, 0.f) + 1e-5f);
    }
    auto centre = [&](int kb) {
#pragma unroll
      for (int i = kb * 16; i < kb * 16 + 16; i++) a[i] = bsub2(a[i], (i & 1) ? mp1 : mp0);
    };
    centre(0);
    TR(0);

    const uint32_t xlo = ((sb + 8 * HS + wg * 8192) >> 4) | (1u << 16);

    auto rs64 = [&](float (&acc)[32], int kb, uint32_t blo, bool first) {
#pragma unroll
      for (int kk = 0; kk < 4; kk++)
        wgmma_rs_n64(acc, a[kb * 16 + kk * 4], a[kb * 16 + kk * 4 + 1], a[kb * 16 + kk * 4 + 2], a[kb * 16 + kk * 4 + 3], mkd(blo + kk * 128), !(first && kk == 0));
    };
    auto ss64 = [&](float (&acc)[32], int slot, uint32_t blo) {
#pragma unroll
      for (int kk = 0; kk < 4; kk++) wgmma_ss_n64(acc, mkd(xlo - (8 - slot) * (HS >> 4) + kk * 2), mkd(blo + kk * 128), 1);
    };
    auto mma64 = [&](float (&acc)[32], int s, uint32_t blo) { if (s < 8) rs64(acc, s, blo, s == 0); else ss64(acc, 8, blo); };
    const uint32_t qrow = sb + (warp * 16 + (lane & 15)) * 16 + (lane >> 4) * 2048;
    auto qkv_slice = [&](const float (&acc)[32], int i, int s, int ngrp) {
      if (s >= 1 && s <= ngrp) {
        const int t = s - 1, c0 = 8 * i + 2 * t;
        const uint32_t r0 = pack2(acc[8 * t] * rs0, acc[8 * t + 1] * rs0), r1 = pack2(acc[8 * t + 2] * rs1, acc[8 * t + 3] * rs1);
        if (c0 < 26) stsm4(qrow + c0 * 2048, r0, r1, pack2(acc[8 * t + 4] * rs0, acc[8 * t + 5] * rs0), pack2(acc[8 * t + 6] * rs1, acc[8 * t + 7] * rs1));
        else stsm2(qrow + c0 * 2048, r0, r1);
      }
      if (s == ngrp) {
        fence_async_smem();
        __syncwarp();
        if (lane == 0) mbar_arrive(bars + (BAR_QST + i) * 8);
      }
    };
    const float rh0 = 0.5f * rs0, rh1 = 0.5f * rs1;
    auto sig_slice = [&](const float (&acc)[32], int s) {
      if (s >= 1) {
#pragma unroll
        for (int e = 2 * (s - 1); e < 2 * s; e++) {
          const float r = (e & 1) ? rh1 : rh0;
          sg[e] = pack2(fmaf(tanh_hw(acc[2 * e] * r), r, r), fmaf(tanh_hw(acc[2 * e + 1] * r), r, r));
        }
      }
    };
    auto h_val = [&](const float (&acc)[32], int e) { return pack2(bf_lo(sg[e]) * acc[2 * e], bf_hi(sg[e]) * acc[2 * e + 1]); };
    auto load_h = [&](int pos) {
#pragma unroll
      for (int kk = (pos & 1) * 2; kk < (pos & 1) * 2 + 2; kk++) {
        const int kb = pos >> 1;
        ldsm4(rowa + kb * HS + (swz ^ (kk << 5)), a[kb * 16 + kk * 4], a[kb * 16 + kk * 4 + 1], a[kb * 16 + kk * 4 + 2], a[kb * 16 + kk * 4 + 3]);
      }
    };

    mbar_wait(bars + BAR_FULL * 8, 0);
    TR(1);
    run_pass<9, 0>(R, false, accB, [&](int s, uint32_t b) { mma64(accA, s, b); }, [&](int s) {
      if (s < 7) centre(s + 1);
      if (s == 6) {
#pragma unroll
        for (int i = 0; i < 16; i++) sg[i] = bsub2(sg[i], (i & 1) ? mp1 : mp0);
#pragma unroll
        for (int kk = 0; kk < 4; kk++) stsm4(rowa + 8 * HS + (swz ^ (kk << 5)), sg[kk * 4], sg[kk * 4 + 1], sg[kk * 4 + 2], sg[kk * 4 + 3]);
        fence_async_smem();
      }
      if (s == 7) asm volatile("bar.sync %0, 128;" ::"r"(1 + wg) : "memory");
    });
    TR(2);
    run_pass<9, 1>(R, false, accA, [&](int s, uint32_t b) { mma64(accB, s, b); }, [&](int s) { qkv_slice(accA, 0, s, 4); });
    TR(3);
    run_pass<9, 2>(R, false, accB, [&](int s, uint32_t b) { mma64(accA, s, b); }, [&](int s) {
      qkv_slice(accB, 1, s, 4);
      if (s == 8) mbar_wait(bars + BAR_W24 * 8, 0);
    });
    TR(4);
    {
      constexpr uint32_t wlo = ((sb + OFF_W24) >> 4) | (8u << 16);
      wg_fence();
#pragma unroll
      for (int k = 0; k < 36; k++) {
        if (k < 32) wgmma_rs_n24(accB, a[k * 4], a[k * 4 + 1], a[k * 4 + 2], a[k * 4 + 3], mkd24(wlo + k * 16), k != 0);
        else wgmma_ss_n24(accB, mkd(xlo + (k - 32) * 2), mkd24(wlo + k * 16), 1);
      }
      wg_commit();
      wg_wait<1>();
      acc_fence(accA);
      if ((threadIdx.x & 127) == 0) mbar_arrive(bars + (BAR_EMPTY + R.prev) * 8);
      R.prev = -1;
#pragma unroll
      for (int s = 1; s <= 4; s++) qkv_slice(accA, 2, s, 4);
    }
    TR(5);
    run_pass<9, 3>(R, false, accB, [&](int s, uint32_t b) { mma64(accA, s, b); }, [&](int s) { qkv_slice(accB, 3, s, 2); });
    TR(6);
    for (int c = 0; c < 8; c++) {
      run_pass<9, 4>(R, false, accA, [&](int s, uint32_t b) { mma64(accB, s, b); }, [&](int s) { sig_slice(accA, s); });
      TR(7 + 2 * c);
      run_pass<9, 5>(R, false, accB, [&](int s, uint32_t b) { mma64(accA, s, b); }, [&](int s) {
        if (s == 1 && (c == 0 || c >= 6)) mbar_wait(bars + (c ? BAR_ATD - 6 + c : BAR_QFREE) * 8, 0);
        if (s >= 1 && s <= 7 && (s & 1)) {
          const int t = s >> 1;
          stsm4(rowa + c * HS + (swz ^ (t << 5)), h_val(accB, 4 * t), h_val(accB, 4 * t + 1), h_val(accB, 4 * t + 2), h_val(accB, 4 * t + 3));
        }
      });
      TR(8 + 2 * c);
    }
    run_pass<9, 6>(R, false, accA, [&](int s, uint32_t b) { mma64(accB, s, b); }, [&](int s) {
      sig_slice(accA, s);
      if (s == 0) {
        fence_async_smem();
        asm volatile("bar.sync %0, 128;" ::"r"(1 + wg) : "memory");
      }
      if (s >= 2) load_h(s - 2);
      if (s == 6) {
        __syncwarp();
        if (lane == 0) mbar_arrive(bars + BAR_OFREE * 8);
      }
    });
    TR(23);
    constexpr uint32_t worlo = ((sb + OFF_WOR) >> 4) | (512u << 16);
    const int grow = m0 + warp * 16;
    int blk = j;
    auto mmaD = [&](float (&acc)[32], int s, uint32_t blo) {
      if (s < 6) rs64(acc, s, blo, s == 0);
      else if (s < 8) ss64(acc, s, blo);
      else if (s == 8) rs64(acc, 6, blo, false);
      else {
        rs64(acc, 7, blo, false);
        wgmma_rs_n64(acc, sg[16], sg[17], 0u, 0u, mkd_sbo0(worlo + blk * 64), 1);
      }
    };
    auto flush_store = [&](const float (&acc)[32], int slot, int t) {
      stsm4(rowa + slot * HS + (swz ^ (t << 5)), pack2(acc[8 * t], acc[8 * t + 1]), pack2(acc[8 * t + 2], acc[8 * t + 3]),
            pack2(acc[8 * t + 4], acc[8 * t + 5]), pack2(acc[8 * t + 6], acc[8 * t + 7]));
    };
    auto flush_issue = [&](int slot, int cb) {
      fence_async_smem();
      __syncwarp();
      if (elect()) { tma2d_red(&mp.out, sb + slot * HS + warp * 2048, cb * 64, grow); bulk_commit(); }
    };
    run_pass<10, 7>(R, false, accB, [&](int s, uint32_t b) { mmaD(accA, s, b); }, [&](int s) {
      if (s < 5) load_h(7 + s);
      if (s >= 1 && s <= 4) {
#pragma unroll
        for (int e = 4 * (s - 1); e < 4 * s; e++) a[96 + e] = h_val(accB, e);
      }
      if (s == 7) {
        mbar_wait(bars + BAR_WOR * 8, 0);
        mbar_wait(bars + BAR_O * 8, 0);
        fence_async_gmem();
        const uint32_t oa = sb + (warp * 16 + (lane & 15)) * 144;
#pragma unroll
        for (int kk = 0; kk < 4; kk++) ldsm4(oa + kk * 32 + (lane >> 4) * 16, a[112 + kk * 4], a[113 + kk * 4], a[114 + kk * 4], a[115 + kk * 4]);
        ldsm2(oa + 128, sg[16], sg[17]);
      }
    });
    TR(24);
    for (int p = 1; p < 9; p += 2) {
      int pb = blk; blk = (blk == 8) ? 0 : blk + 1;
      run_pass<10, 8>(R, false, accA, [&](int s, uint32_t b) { mmaD(accB, s, b); }, [&](int s) {
        const int slot = (p == 5) ? 8 : (p == 7) ? 1 : p + 1;
        if (s >= 1 && s <= 4) flush_store(accA, slot, s - 1);
        if (s == 5) flush_issue(slot, pb);
      });
      TR(24 + p);
      pb = blk; blk = (blk == 8) ? 0 : blk + 1;
      run_pass<10, 9>(R, p == 7, accB, [&](int s, uint32_t b) { mmaD(accA, s, b); }, [&](int s) {
        const int slot = (p < 5) ? p + 2 : p - 5;
        if (s == 0 && p == 7) { asm volatile("cp.async.bulk.wait_group.read 5;" ::: "memory"); __syncwarp(); }
        if (s >= 1 && s <= 4) flush_store(accB, slot, s - 1);
        if (s == 5) flush_issue(slot, pb);
      });
      TR(25 + p);
    }
    wg_wait<0>();
    acc_fence(accA);
    TR(33);
#pragma unroll
    for (int t = 0; t < 4; t++) flush_store(accA, 3, t);
    flush_issue(3, blk);
    bulk_wait_read_all();
    TR(34);
  } else {
    asm volatile("setmaxnreg.dec.sync.aligned.u32 40;\n");
    if (warp == 8) {
      int st = 0; uint32_t ph = 1;
      auto stage = [&](const CUtensorMap* w, int c0, int c1) {
        mbar_wait(bars + (BAR_EMPTY + st) * 8, ph);
        const uint32_t fb = bars + (BAR_FULL + st) * 8;
        if (elect()) {
          mbar_expect(fb, SLOT);
          tma2d(sb + OFF_RING + st * SLOT, w, c0, c1, fb);
        }
        st++;
        if (st == NSLOT) { st = 0; ph ^= 1; }
      };
      int blk = j;
#pragma unroll 1
      for (int p = 0; p < 30; p++) {
        const CUtensorMap* w; int c0, c1 = 0;
        if (p < 3) { w = &mp.wqkv; c0 = j * 192 + p * 64; }
        else if (p < 21) { w = (p & 1) ? &mp.wg : &mp.wu; c0 = j * 576 + ((p - 3) >> 1) * 64; }
        else { w = &mp.wd; c0 = blk * 64; c1 = j * 576; }
#pragma unroll kPUnroll
        for (int kb = 0; kb < 9; kb++) stage(w, c0, c1 + kb * 64);
        if (p >= 21) {
          stage(&mp.woa, c0, j * 72);
          blk = (blk == 8) ? 0 : blk + 1;
        } else if (p == 3 && elect()) {
          mbar_expect(bars + BAR_WOR * 8, 9 * 1024);
#pragma unroll 1
          for (int b = 0; b < 9; b++) tma2d(sb + OFF_WOR + b * 1024, &mp.wob, b * 64, j * 72 + 64, bars + BAR_WOR * 8);
        }
      }
    } else {
      const int aw = warp - 9;
      const unsigned target = (*(volatile unsigned*)&g_epoch + 1) * 8;
      mbar_wait(bars + BAR_XDONE * 8, 0);
      {
        const char* src = reinterpret_cast<const char*>(wqkv) + 3072 + j * 48;
        const int t = aw * 32 + lane, r = t / 3, ng = t - r * 3;
#pragma unroll 6
        for (int i = 0; i < 18; i++)
          asm volatile("cp.async.cg.shared.global [%0], [%1], 16;" ::"r"(sb + OFF_W24 + ng * 9216 + (i * 32 + r) * 16),
                       "l"(src + (size_t)(i * 32 + r) * (3 * DM * 2) + ng * 16) : "memory");
        const size_t base = (size_t)(m0 + j * 16) * (DM / 8);
#pragma unroll 4
        for (int i = t; i < 16 * (DM / 8); i += 96) outg[base + i] = xg[base + i];
        asm volatile("cp.async.wait_all;" ::: "memory");
        fence_async_smem();
        __syncwarp();
        if (lane == 0) mbar_arrive(bars + BAR_W24 * 8);
        asm volatile("bar.sync 3, 96;" ::: "memory");
      }
      auto load_step = [&](int t) {
        const uint32_t bar = bars + (BAR_ATI + (t & 1)) * 8, dst = sb + OFF_ATT + (t & 1) * HS;
        const int r2 = (m0 + t * 24) * 2;
        mbar_expect(bar, 9 * (38 + 38 + 24) * 16);
        tma2d(dst, &mp.lkv, r2 - 28, 72 + j * 9, bar);
        tma2d(dst + AV, &mp.lkv, r2 - 28, 144 + j * 9, bar);
        tma2d(dst + AQ, &mp.lq, r2, j * 9, bar);
      };
      if (aw == 0) {
#pragma unroll
        for (int i = 0; i < 4; i++) {
          mbar_wait(bars + (BAR_QST + i) * 8, 0);
          if (elect()) {
            if (i < 3) tma2d_store(&mp.qs8, sb + i * HS, m0 * 2, j * 24 + i * 8);
            else tma2d_store(&mp.qs3, sb + i * HS, m0 * 2, 192 + j * 3);
            bulk_commit();
          }
        }
        bulk_wait_all();
        __syncwarp();
        if (lane == 0) {
          mbar_arrive(bars + BAR_QFREE * 8);
          red_release(&g_cnt[m * 32], 1);
        }
        if (lane < 2) wait_counter(&g_cnt[(lane && m ? m - 1 : m) * 32], target);
        __syncwarp();
        fence_async_gmem();
        if (elect()) { load_step(0); load_step(1); }
      }
      const int g = lane & 7, hh = lane >> 3;
      const float sc = 0.23570226039551584f * 1.4426950408889634f;
#pragma unroll 1
      for (int t = 0; t < 6; t++) {
        mbar_wait(bars + (BAR_ATI + (t & 1)) * 8, (t >> 1) & 1);
        if (t < 5 || aw == 0) {
          const int lr = aw * 8 + g, row = t * 24 + lr;
          const uint32_t base = sb + OFF_ATT + (t & 1) * HS + lr * 16;
          float p[8] = {};
          uint32_t h8 = hh * 8;
          asm volatile("" : "+r"(h8));
          const uint32_t po0 = (0x70503000u >> h8) & 255, po1 = (0x80482810u >> h8) & 255;
          const uint32_t po2 = (0x88604018u >> h8) & 255, po3 = (0x6C682420u >> h8) & 255;
          auto qk = [&](auto nw, uint32_t po) {
            constexpr int N = decltype(nw)::value;
            uint32_t u[N]; float q[2 * N];
            lds<N>(base + AQ + (po >> 4) * 384 + (po & 15), u);
#pragma unroll
            for (int i = 0; i < N; i++) { q[2 * i] = bf_lo(u[i]); q[2 * i + 1] = bf_hi(u[i]); }
            const uint32_t ka = base + (po >> 4) * 608 + (po & 15);
#pragma unroll
            for (int w = 0; w < 8; w++) {
              lds<N>(ka + (14 - 2 * w) * 16, u);
#pragma unroll
              for (int i = 0; i < N; i++) { p[w] = fmaf(q[2 * i], bf_lo(u[i]), p[w]); p[w] = fmaf(q[2 * i + 1], bf_hi(u[i]), p[w]); }
            }
          };
          qk(IC<4>(), po0); qk(IC<2>(), po1); qk(IC<2>(), po2); qk(IC<1>(), po3);
          if (m0 + t == 0) {
#pragma unroll
            for (int w = 1; w < 8; w++) if (row < 2 * w) p[w] = -INFINITY;
          }
          const float mx = fmaxf(fmaxf(fmaxf(p[0], p[1]), fmaxf(p[2], p[3])), fmaxf(fmaxf(p[4], p[5]), fmaxf(p[6], p[7])));
          float l = 0.f;
#pragma unroll
          for (int w = 0; w < 8; w++) { p[w] = ex2((p[w] - mx) * sc); l += p[w]; }
          l = __fdividef(1.f, l);
#pragma unroll
          for (int w = 0; w < 8; w++) p[w] *= l;
          char* op = reinterpret_cast<char*>(g_o + (blockIdx.x * 128 + row) * 36);
          auto pv = [&](auto nw, uint32_t po) {
            constexpr int N = decltype(nw)::value;
            uint32_t u[2][N]; float o[2 * N] = {};
            const uint32_t va = base + AV + (po >> 4) * 608 + (po & 15);
            lds<N>(va + 14 * 16, u[0]);
#pragma unroll
            for (int w = 0; w < 8; w++) {
              if (w < 7) lds<N>(va + (12 - 2 * w) * 16, u[(w + 1) & 1]);
#pragma unroll
              for (int i = 0; i < N; i++) { o[2 * i] = fmaf(p[w], bf_lo(u[w & 1][i]), o[2 * i]); o[2 * i + 1] = fmaf(p[w], bf_hi(u[w & 1][i]), o[2 * i + 1]); }
            }
            if (N == 4) *reinterpret_cast<uint4*>(op + po) = make_uint4(pack2(o[0], o[1]), pack2(o[2 % (2 * N)], o[3 % (2 * N)]), pack2(o[4 % (2 * N)], o[5 % (2 * N)]), pack2(o[6 % (2 * N)], o[7 % (2 * N)]));
            else if (N == 2) *reinterpret_cast<uint2*>(op + po) = make_uint2(pack2(o[0], o[1]), pack2(o[2 % (2 * N)], o[3 % (2 * N)]));
            else *reinterpret_cast<uint32_t*>(op + po) = pack2(o[0], o[1]);
          };
          pv(IC<4>(), po0); pv(IC<2>(), po1); pv(IC<2>(), po2); pv(IC<1>(), po3);
        }
        asm volatile("bar.sync 3, 96;" ::: "memory");
        if (aw == 0 && elect()) {
          if (t < 4) load_step(t + 2); else mbar_arrive(bars + (BAR_ATD + t - 4) * 8);
        }
      }
      __threadfence();
      asm volatile("bar.sync 3, 96;" ::: "memory");
      if (aw == 0 && lane == 0) {
        mbar_wait(bars + BAR_OFREE * 8, 0);
        fence_async_gmem();
        mbar_expect(bars + BAR_O * 8, OTILE);
        bulk_g2s(sb, g_o + blockIdx.x * 128 * 36, OTILE, bars + BAR_O * 8);
      }
      if (aw == 0 && lane == 0) {
        if (atomicInc(&g_done, 127u) == 127u) atomicAdd(&g_epoch, 1u);
      }
    }
  }
}

typedef CUresult (*EncodeFn)(CUtensorMap*, CUtensorMapDataType, cuuint32_t, void*, const cuuint64_t*, const cuuint64_t*, const cuuint32_t*,
                             const cuuint32_t*, CUtensorMapInterleave, CUtensorMapSwizzle, CUtensorMapL2promotion, CUtensorMapFloatOOBfill);

#define PROMO CU_TENSOR_MAP_L2_PROMOTION_L2_128B
void encode2(EncodeFn fn, CUtensorMap* m, const void* p, uint64_t cols, uint64_t rows, uint32_t bc, uint32_t br, bool raw = false) {
  const cuuint64_t d[2] = {cols, rows}, s[1] = {cols * (raw ? 8 : 2)};
  const cuuint32_t b[2] = {bc, br}, es[2] = {1, 1};
  fn(m, raw ? CU_TENSOR_MAP_DATA_TYPE_UINT64 : CU_TENSOR_MAP_DATA_TYPE_BFLOAT16, 2, const_cast<void*>(p), d, s, b, es, CU_TENSOR_MAP_INTERLEAVE_NONE,
     raw ? CU_TENSOR_MAP_SWIZZLE_NONE : CU_TENSOR_MAP_SWIZZLE_128B, PROMO, CU_TENSOR_MAP_FLOAT_OOB_FILL_NONE);
}

}

extern "C" void kernel_launch(void* const* d_in, const int* in_sizes, int n_in, void* d_out, int out_size) {
  void* fp = nullptr;
  cudaDriverEntryPointQueryResult qr;
  cudaGetDriverEntryPoint("cuTensorMapEncodeTiled", &fp, cudaEnableDefault, &qr);
  EncodeFn fn = (EncodeFn)fp;
  void* qkv = nullptr;
  cudaGetSymbolAddress(&qkv, g_qkv);
  Maps mp;
  encode2(fn, &mp.x, d_in[0], DM, SEQ, 64, NXB == 18 ? 64 : 128);
  encode2(fn, &mp.wqkv, d_in[1], 3 * DM, DM, 64, 64);
  encode2(fn, &mp.wg, d_in[4], FF, DM, 64, 64);
  encode2(fn, &mp.wu, d_in[5], FF, DM, 64, 64);
  encode2(fn, &mp.wd, d_in[6], DM, FF, 64, 64);
  encode2(fn, &mp.woa, d_in[2], DM, DM, 64, 64);
  encode2(fn, &mp.wob, d_in[2], DM, DM, 64, 8);
  encode2(fn, &mp.out, d_out, DM, SEQ, 64, 16);
  encode2(fn, &mp.qs8, qkv, 2 * SEQ, 216, 256, 8, true);
  encode2(fn, &mp.qs3, qkv, 2 * SEQ, 216, 256, 3, true);
  encode2(fn, &mp.lkv, qkv, 2 * SEQ, 216, 76, 9, true);
  encode2(fn, &mp.lq, qkv, 2 * SEQ, 216, 48, 9, true);
  cudaFuncSetAttribute(fused_kernel, cudaFuncAttributeMaxDynamicSharedMemorySize, SMEM_BYTES);
  fused_kernel<<<128, 384, SMEM_BYTES, cudaStreamPerThread>>>(mp, (const uint4*)d_in[0], d_in[1], (uint4*)d_out);
}
```

```cpp
#include <cuda_runtime.h>
#include <cuda.h>
#include <cuda_bf16.h>
#include <stdint.h>

namespace {

constexpr int SEQ = 2048, DM = 576, FF = 4608;
constexpr int NSLOT = 9;
constexpr int SLOT = 8192;
constexpr int HS = 16384;
constexpr int OFF_RING = 9 * HS;
constexpr int OFF_WOR = OFF_RING + NSLOT * SLOT;
constexpr int OFF_BAR = OFF_WOR + 9 * 1024;
constexpr int SMEM_BYTES = OFF_BAR + 512;
constexpr int OFF_W24 = 4 * HS;
constexpr int OTILE = 128 * 144;
constexpr int OFF_AK = 6 * HS, OFF_AQ = OFF_AK + 8960, OFF_AV = 7 * HS;
constexpr int BAR_FULL = 0, BAR_EMPTY = 9, BAR_X = 18, BAR_WOR = 36, BAR_XDONE = 37, BAR_W24 = 38, BAR_QST = 39, BAR_QFREE = 43,
              BAR_ATI = 44, BAR_ATD = 46, BAR_O = 48, BAR_OFREE = 49;
#define XT 256
#define NXB 9
#define NAP 64
#define PFW 4
#define CREG "232"
#define AREG "40"
#define PUNROLL 1
#define QKU 1
constexpr int kQKU = QKU;
constexpr int kPUnroll = PUNROLL;
constexpr int SPIN_LIMIT = 1 << 22;

__device__ uint4 g_qkv[216 * SEQ];
__device__ uint32_t g_o[128 * 128 * 36];
__device__ unsigned g_cnt[16 * 32];
__device__ unsigned g_done;
__device__ unsigned g_epoch;
#define TR(i)
#define TRG(i)
#define TRC(i)

__device__ __forceinline__ uint32_t smem_u32(const void* p) { return (uint32_t)__cvta_generic_to_shared(p); }
__device__ __forceinline__ void wg_fence() { asm volatile("wgmma.fence.sync.aligned;\n" ::: "memory"); }
__device__ __forceinline__ void wg_commit() { asm volatile("wgmma.commit_group.sync.aligned;\n" ::: "memory"); }
template <int N> __device__ __forceinline__ void wg_wait() { asm volatile("wgmma.wait_group.sync.aligned %0;\n" ::"n"(N) : "memory"); }
__device__ __forceinline__ void mbar_init(uint32_t a, int c) { asm volatile("mbarrier.init.shared::cta.b64 [%0], %1;" ::"r"(a), "r"(c) : "memory"); }
__device__ __forceinline__ void mbar_expect(uint32_t a, uint32_t b) { asm volatile("mbarrier.arrive.expect_tx.shared::cta.b64 _, [%0], %1;" ::"r"(a), "r"(b) : "memory"); }
__device__ __forceinline__ void mbar_arrive(uint32_t a) { asm volatile("mbarrier.arrive.shared::cta.b64 _, [%0];" ::"r"(a) : "memory"); }
__device__ __forceinline__ void mbar_wait(uint32_t a, uint32_t par) {
  uint32_t ok; int it = 0;
  while (true) {
    asm volatile("{\n.reg .pred p;\nmbarrier.try_wait.parity.shared::cta.b64 p, [%1], %2;\nselp.u32 %0,1,0,p;\n}\n" : "=r"(ok) : "r"(a), "r"(par) : "memory");
    if (ok) break;
    if (++it > SPIN_LIMIT) __trap();
  }
}
__device__ __forceinline__ uint32_t mbar_try(uint32_t a, uint32_t par) {
  uint32_t ok;
  asm volatile("{\n.reg .pred p;\nmbarrier.try_wait.parity.shared::cta.b64 p, [%1], %2;\nselp.u32 %0,1,0,p;\n}\n" : "=r"(ok) : "r"(a), "r"(par) : "memory");
  return ok;
}
__device__ __forceinline__ void fence_mbar_init() { asm volatile("fence.mbarrier_init.release.cluster;" ::: "memory"); }
__device__ __forceinline__ void fence_async_smem() { asm volatile("fence.proxy.async.shared::cta;\n" ::: "memory"); }
__device__ __forceinline__ void fence_async_gmem() { asm volatile("fence.proxy.async.global;\n" ::: "memory"); }
__device__ __forceinline__ void tma2d(uint32_t dst, const CUtensorMap* m, int c0, int c1, uint32_t bar) {
  asm volatile("cp.async.bulk.tensor.2d.shared::cluster.global.mbarrier::complete_tx::bytes [%0], [%1, {%3, %4}], [%2];" ::"r"(dst), "l"(m), "r"(bar), "r"(c0), "r"(c1) : "memory");
}
__device__ __forceinline__ void bulk_g2s(uint32_t dst, const void* src, uint32_t bytes, uint32_t bar) {
  asm volatile("cp.async.bulk.shared::cluster.global.mbarrier::complete_tx::bytes [%0], [%1], %2, [%3];" ::"r"(dst), "l"(src), "r"(bytes), "r"(bar) : "memory");
}
__device__ __forceinline__ void tma2d_store(const CUtensorMap* m, uint32_t src, int c0, int c1) {
  asm volatile("cp.async.bulk.tensor.2d.global.shared::cta.tile.bulk_group [%0, {%2, %3}], [%1];" ::"l"(m), "r"(src), "r"(c0), "r"(c1) : "memory");
}
__device__ __forceinline__ bool elect() {
  uint32_t p;
  asm volatile("{\n.reg .pred p;\nelect.sync _|p, 0xffffffff;\nselp.u32 %0, 1, 0, p;\n}\n" : "=r"(p));
  return p;
}
__device__ __forceinline__ void tma2d_red(const CUtensorMap* m, uint32_t src, int c0, int c1) {
  asm volatile("cp.reduce.async.bulk.tensor.2d.global.shared::cta.add.tile.bulk_group [%0, {%2, %3}], [%1];" ::"l"(m), "r"(src), "r"(c0), "r"(c1) : "memory");
}
__device__ __forceinline__ void bulk_commit() { asm volatile("cp.async.bulk.commit_group;" ::: "memory"); }
__device__ __forceinline__ void bulk_wait_all() { asm volatile("cp.async.bulk.wait_group 0;" ::: "memory"); }
__device__ __forceinline__ void bulk_wait_read_all() { asm volatile("cp.async.bulk.wait_group.read 0;" ::: "memory"); }
__device__ __forceinline__ void ldsm4(uint32_t addr, uint32_t& r0, uint32_t& r1, uint32_t& r2, uint32_t& r3) {
  asm volatile("ldmatrix.sync.aligned.m8n8.x4.shared.b16 {%0,%1,%2,%3}, [%4];" : "=r"(r0), "=r"(r1), "=r"(r2), "=r"(r3) : "r"(addr) : "memory");
}
__device__ __forceinline__ void ldsm2(uint32_t addr, uint32_t& r0, uint32_t& r1) {
  asm volatile("ldmatrix.sync.aligned.m8n8.x2.shared.b16 {%0,%1}, [%2];" : "=r"(r0), "=r"(r1) : "r"(addr) : "memory");
}
__device__ __forceinline__ void stsm4(uint32_t addr, uint32_t r0, uint32_t r1, uint32_t r2, uint32_t r3) {
  asm volatile("stmatrix.sync.aligned.m8n8.x4.shared.b16 [%0], {%1,%2,%3,%4};" ::"r"(addr), "r"(r0), "r"(r1), "r"(r2), "r"(r3) : "memory");
}
__device__ __forceinline__ void stsm2(uint32_t addr, uint32_t r0, uint32_t r1) {
  asm volatile("stmatrix.sync.aligned.m8n8.x2.shared.b16 [%0], {%1,%2};" ::"r"(addr), "r"(r0), "r"(r1) : "memory");
}
__device__ __forceinline__ void bulk_prefetch(const void* p, uint32_t bytes) { asm volatile("cp.async.bulk.prefetch.L2.global [%0], %1;" ::"l"(p), "r"(bytes) : "memory"); }
template <int N> __device__ __forceinline__ void lds(uint32_t addr, uint32_t* v) {
  if (N == 4) asm volatile("ld.shared.v4.b32 {%0,%1,%2,%3}, [%4];" : "=r"(v[0]), "=r"(v[1]), "=r"(v[2]), "=r"(v[3]) : "r"(addr));
  else if (N == 2) asm volatile("ld.shared.v2.b32 {%0,%1}, [%2];" : "=r"(v[0]), "=r"(v[1]) : "r"(addr));
  else asm volatile("ld.shared.b32 %0, [%1];" : "=r"(v[0]) : "r"(addr));
}
__device__ __forceinline__ uint32_t pack2(float lo, float hi) { uint32_t r; asm("cvt.rn.bf16x2.f32 %0, %1, %2;" : "=r"(r) : "f"(hi), "f"(lo)); return r; }
__device__ __forceinline__ float bf_lo(uint32_t v) { return __uint_as_float(v << 16); }
__device__ __forceinline__ float bf_hi(uint32_t v) { return __uint_as_float(v & 0xffff0000u); }
__device__ __forceinline__ uint32_t bsub2(uint32_t a, uint32_t b) { uint32_t r; asm("sub.rn.bf16x2 %0, %1, %2;" : "=r"(r) : "r"(a), "r"(b)); return r; }
__device__ __forceinline__ uint32_t bmul2(uint32_t a, uint32_t b) { uint32_t r; asm("mul.rn.bf16x2 %0, %1, %2;" : "=r"(r) : "r"(a), "r"(b)); return r; }
__device__ __forceinline__ float tanh_hw(float x) { float y; asm("tanh.approx.f32 %0, %1;" : "=f"(y) : "f"(x)); return y; }
__device__ __forceinline__ float ex2(float x) { float y; asm("ex2.approx.ftz.f32 %0, %1;" : "=f"(y) : "f"(x)); return y; }
__device__ __forceinline__ unsigned ld_acquire(const unsigned* p) { unsigned v; asm volatile("ld.acquire.gpu.global.u32 %0, [%1];" : "=r"(v) : "l"(p) : "memory"); return v; }
__device__ __forceinline__ void red_release(unsigned* p, unsigned v) { asm volatile("red.release.gpu.global.add.u32 [%0], %1;" ::"l"(p), "r"(v) : "memory"); }
__device__ __forceinline__ void wait_counter(const unsigned* p, unsigned target) {
  int it = 0;
  while ((int)(ld_acquire(p) - target) < 0) { __nanosleep(32); if (++it > SPIN_LIMIT) __trap(); }
}
__device__ __forceinline__ void mma16816(float (&d)[4], uint32_t a0, uint32_t a1, uint32_t a2, uint32_t a3, uint32_t b0, uint32_t b1) {
  asm volatile("mma.sync.aligned.m16n8k16.row.col.f32.bf16.bf16.f32 {%0,%1,%2,%3}, {%4,%5,%6,%7}, {%8,%9}, {%0,%1,%2,%3};"
               : "+f"(d[0]), "+f"(d[1]), "+f"(d[2]), "+f"(d[3]) : "r"(a0), "r"(a1), "r"(a2), "r"(a3), "r"(b0), "r"(b1));
}
__device__ __forceinline__ void mma1688(float (&d)[4], uint32_t a0, uint32_t a1, uint32_t b0) {
  asm volatile("mma.sync.aligned.m16n8k8.row.col.f32.bf16.bf16.f32 {%0,%1,%2,%3}, {%4,%5}, {%6}, {%0,%1,%2,%3};"
               : "+f"(d[0]), "+f"(d[1]), "+f"(d[2]), "+f"(d[3]) : "r"(a0), "r"(a1), "r"(b0));
}

__device__ __forceinline__ void wgmma_rs_n64(float (&d)[32], uint32_t a0, uint32_t a1, uint32_t a2, uint32_t a3, uint64_t db, int sd) {
  asm volatile("{\n.reg .pred p;\nsetp.ne.b32 p, %37, 0;\n"
    "wgmma.mma_async.sync.aligned.m64n64k16.f32.bf16.bf16 {%0, %1, %2, %3, %4, %5, %6, %7, %8, %9, %10, %11, %12, %13, %14, %15, %16, %17, %18, %19, %20, %21, %22, %23, %24, %25, %26, %27, %28, %29, %30, %31}, {%32, %33, %34, %35}, %36, p, 1, 1, 1;\n"
    "}\n"
    : "+f"(d[0]), "+f"(d[1]), "+f"(d[2]), "+f"(d[3]), "+f"(d[4]), "+f"(d[5]), "+f"(d[6]), "+f"(d[7]), "+f"(d[8]), "+f"(d[9]), "+f"(d[10]), "+f"(d[11]), "+f"(d[12]), "+f"(d[13]), "+f"(d[14]), "+f"(d[15]), "+f"(d[16]), "+f"(d[17]), "+f"(d[18]), "+f"(d[19]), "+f"(d[20]), "+f"(d[21]), "+f"(d[22]), "+f"(d[23]), "+f"(d[24]), "+f"(d[25]), "+f"(d[26]), "+f"(d[27]), "+f"(d[28]), "+f"(d[29]), "+f"(d[30]), "+f"(d[31])
    : "r"(a0), "r"(a1), "r"(a2), "r"(a3), "l"(db), "r"(sd));
}

__device__ __forceinline__ void wgmma_ss_n64(float (&d)[32], uint64_t da, uint64_t db, int sd) {
  asm volatile("{\n.reg .pred p;\nsetp.ne.b32 p, %34, 0;\n"
    "wgmma.mma_async.sync.aligned.m64n64k16.f32.bf16.bf16 {%0, %1, %2, %3, %4, %5, %6, %7, %8, %9, %10, %11, %12, %13, %14, %15, %16, %17, %18, %19, %20, %21, %22, %23, %24, %25, %26, %27, %28, %29, %30, %31}, %32, %33, p, 1, 1, 0, 1;\n"
    "}\n"
    : "+f"(d[0]), "+f"(d[1]), "+f"(d[2]), "+f"(d[3]), "+f"(d[4]), "+f"(d[5]), "+f"(d[6]), "+f"(d[7]), "+f"(d[8]), "+f"(d[9]), "+f"(d[10]), "+f"(d[11]), "+f"(d[12]), "+f"(d[13]), "+f"(d[14]), "+f"(d[15]), "+f"(d[16]), "+f"(d[17]), "+f"(d[18]), "+f"(d[19]), "+f"(d[20]), "+f"(d[21]), "+f"(d[22]), "+f"(d[23]), "+f"(d[24]), "+f"(d[25]), "+f"(d[26]), "+f"(d[27]), "+f"(d[28]), "+f"(d[29]), "+f"(d[30]), "+f"(d[31])
    : "l"(da), "l"(db), "r"(sd));
}

__device__ __forceinline__ void wgmma_rs_n24(float (&d)[32], uint32_t a0, uint32_t a1, uint32_t a2, uint32_t a3, uint64_t db, int sd) {
  asm volatile("{\n.reg .pred p;\nsetp.ne.b32 p, %17, 0;\n"
    "wgmma.mma_async.sync.aligned.m64n24k16.f32.bf16.bf16 {%0, %1, %2, %3, %4, %5, %6, %7, %8, %9, %10, %11}, {%12, %13, %14, %15}, %16, p, 1, 1, 1;\n"
    "}\n"
    : "+f"(d[0]), "+f"(d[1]), "+f"(d[2]), "+f"(d[3]), "+f"(d[4]), "+f"(d[5]), "+f"(d[6]), "+f"(d[7]), "+f"(d[8]), "+f"(d[9]), "+f"(d[10]), "+f"(d[11])
    : "r"(a0), "r"(a1), "r"(a2), "r"(a3), "l"(db), "r"(sd));
}

__device__ __forceinline__ void wgmma_ss_n24(float (&d)[32], uint64_t da, uint64_t db, int sd) {
  asm volatile("{\n.reg .pred p;\nsetp.ne.b32 p, %14, 0;\n"
    "wgmma.mma_async.sync.aligned.m64n24k16.f32.bf16.bf16 {%0, %1, %2, %3, %4, %5, %6, %7, %8, %9, %10, %11}, %12, %13, p, 1, 1, 0, 1;\n"
    "}\n"
    : "+f"(d[0]), "+f"(d[1]), "+f"(d[2]), "+f"(d[3]), "+f"(d[4]), "+f"(d[5]), "+f"(d[6]), "+f"(d[7]), "+f"(d[8]), "+f"(d[9]), "+f"(d[10]), "+f"(d[11])
    : "l"(da), "l"(db), "r"(sd));
}

__device__ __forceinline__ uint64_t mkd(uint32_t lo) { return ((uint64_t)0x40000040u << 32) | (uint64_t)lo; }
__device__ __forceinline__ uint64_t mkd_sbo0(uint32_t lo) { return ((uint64_t)0x40000000u << 32) | (uint64_t)lo; }
__device__ __forceinline__ uint64_t mkd24(uint32_t lo) { return ((uint64_t)(9216 >> 4) << 32) | (uint64_t)lo; }

constexpr uint32_t sb = 1024;
constexpr uint32_t bars = sb + OFF_BAR;
constexpr uint32_t RING_LO = ((sb + OFF_RING) >> 4) | (512u << 16);

__device__ __forceinline__ void acc_fence(float (&d)[32]) {
  asm volatile("" : "+f"(d[0]), "+f"(d[1]), "+f"(d[2]), "+f"(d[3]), "+f"(d[4]), "+f"(d[5]), "+f"(d[6]), "+f"(d[7]), "+f"(d[8]), "+f"(d[9]), "+f"(d[10]), "+f"(d[11]), "+f"(d[12]), "+f"(d[13]), "+f"(d[14]), "+f"(d[15]), "+f"(d[16]), "+f"(d[17]), "+f"(d[18]), "+f"(d[19]), "+f"(d[20]), "+f"(d[21]), "+f"(d[22]), "+f"(d[23]), "+f"(d[24]), "+f"(d[25]), "+f"(d[26]), "+f"(d[27]), "+f"(d[28]), "+f"(d[29]), "+f"(d[30]), "+f"(d[31]) :: "memory");
}

template <int V> struct IC { static constexpr int value = V; };

struct Ring {
  int st, prev;
  uint32_t ph;
};

template <int NST, int ID, class M, class F>
__device__ __forceinline__ void run_pass(Ring& R, bool last, float (&other)[32], M&& mma, F&& slice) {
#pragma unroll
  for (int s = 0; s < NST; s++) {
    const uint32_t blo = RING_LO + R.st * (SLOT >> 4);
    wg_fence();
    mma(s, blo);
    wg_commit();
    const int cur = R.st;
    R.st++;
    if (R.st == NSLOT) { R.st = 0; R.ph ^= 1; }
    if (!(last && s == NST - 1)) mbar_wait(bars + (BAR_FULL + R.st) * 8, R.ph);
    slice(s);
    wg_wait<1>();
    if (s == 0) acc_fence(other);
    if (R.prev >= 0 && (threadIdx.x & 127) == 0) mbar_arrive(bars + (BAR_EMPTY + R.prev) * 8);
    R.prev = cur;
  }
}

struct Maps {
  CUtensorMap x, wqkv, wg, wu, wd, woa, wob, out, qs8, qs3, lkv, lq;
};

__global__ void __launch_bounds__(384, 1)
fused_kernel(const __grid_constant__ Maps mp, const void* __restrict__ wqkv) {
  extern __shared__ __align__(1024) uint8_t smem[];
  const int j = blockIdx.x & 7, m = blockIdx.x >> 3;
  const int m0 = m * 128;
  if (threadIdx.x == XT) {
#pragma unroll
    for (int i = 0; i < 9; i++) {
      const uint32_t b = bars + (BAR_X + i) * 8;
      mbar_init(b, 1);
      fence_mbar_init();
      mbar_expect(b, HS);
      tma2d(sb + i * HS, &mp.x, i * 64, m0, b);
    }
  }
  const int warp = __shfl_sync(0xffffffffu, threadIdx.x >> 5, 0), lane = threadIdx.x & 31;

  asm volatile("" ::: "memory");
  if (lane == 0) {
    if (warp == 9) {
      if (smem_u32(smem) != sb) __trap();
      for (int i = 0; i < NSLOT; i++) { mbar_init(bars + (BAR_FULL + i) * 8, 1); mbar_init(bars + (BAR_EMPTY + i) * 8, 2); }
      fence_mbar_init();
    } else if (warp == 10) {
      mbar_init(bars + BAR_WOR * 8, 1);
      mbar_init(bars + BAR_XDONE * 8, 9);
      mbar_init(bars + BAR_W24 * 8, 3);
      for (int i = 0; i < 4; i++) mbar_init(bars + (BAR_QST + i) * 8, 8);
      mbar_init(bars + BAR_QFREE * 8, 1);
      for (int i = 0; i < 2; i++) { mbar_init(bars + (BAR_ATI + i) * 8, 1); mbar_init(bars + (BAR_ATD + i) * 8, 1); }
      mbar_init(bars + BAR_O * 8, 1);
      mbar_init(bars + BAR_OFREE * 8, 8);
      fence_mbar_init();
    }
  }
  __syncthreads();

  if (warp < 8) {
    asm volatile("setmaxnreg.inc.sync.aligned.u32 " CREG ";\n");
    const int wg = warp >> 2;
    const int lrow = (warp & 3) * 16 + (lane & 15);
    const uint32_t rowa = sb + wg * 8192 + lrow * 128;
    const uint32_t swz = ((lane >> 4) ^ (lrow & 7)) << 4;
    uint32_t a[128];
    uint32_t sg[18];
    float accA[32], accB[32];
    float rs0, rs1;

    Ring R;
    R.st = 0; R.prev = -1; R.ph = 0;
    uint32_t mp0, mp1;
    {
      float cs[2][4] = {}, c1[2][4] = {}, c2[2][4] = {};
      mbar_wait(bars + BAR_X * 8, 0);
      TR(40);
#pragma unroll
      for (int kb = 0; kb <= 9; kb++) {
        uint32_t ok = 1;
        if (kb < 8) ok = mbar_try(bars + (BAR_X + kb + 1) * 8, 0);
        if (kb < 9) {
          if (kb == 8) TR(41);
#pragma unroll
          for (int kk = 0; kk < 4; kk++) {
            uint32_t* r = (kb < 8) ? &a[kb * 16 + kk * 4] : &sg[kk * 4];
            ldsm4(rowa + kb * HS + (swz ^ (kk << 5)), r[0], r[1], r[2], r[3]);
          }
        }
        if (kb > 0) {
#pragma unroll
          for (int kk = 0; kk < 4; kk++) {
            const uint32_t* r = (kb < 9) ? &a[(kb - 1) * 16 + kk * 4] : &sg[kk * 4];
            mma16816(cs[kk & 1], r[0], r[1], r[2], r[3], 0x3f803f80u, 0x3f803f80u);
            mma1688(c1[0], r[0], r[1], r[0]);
            mma1688(c2[0], r[0], r[1], r[1]);
            mma1688(c1[1], r[2], r[3], r[2]);
            mma1688(c2[1], r[2], r[3], r[3]);
          }
        }
        if (!ok) mbar_wait(bars + (BAR_X + kb + 1) * 8, 0);
      }
      __syncwarp();
      if (lane == 0) mbar_arrive(bars + BAR_XDONE * 8);
      const float mu0 = (cs[0][0] + cs[1][0]) * (1.f / DM), mu1 = (cs[0][2] + cs[1][2]) * (1.f / DM);
      mp0 = pack2(mu0, mu0); mp1 = pack2(mu1, mu1);
      const int src = (lane & ~3) | (lane >> 3);
      const float q0 = __shfl_sync(0xffffffffu, (lane & 4) ? c1[0][1] + c1[1][1] : c1[0][0] + c1[1][0], src);
      const float q1 = __shfl_sync(0xffffffffu, (lane & 4) ? c2[0][3] + c2[1][3] : c2[0][2] + c2[1][2], src);
      rs0 = rsqrtf(fmaxf(q0 * (1.f / DM) - mu0 * mu0, 0.f) + 1e-5f);
      rs1 = rsqrtf(fmaxf(q1 * (1.f / DM) - mu1 * mu1, 0.f) + 1e-5f);
    }
    auto centre = [&](int kb) {
#pragma unroll
      for (int i = kb * 16; i < kb * 16 + 16; i++) a[i] = bsub2(a[i], (i & 1) ? mp1 : mp0);
    };
    centre(0);
    centre(1);
    TR(0);

    const uint32_t xlo = ((sb + 8 * HS + wg * 8192) >> 4) | (1u << 16);

    auto rs64 = [&](float (&acc)[32], int kb, uint32_t blo, bool first) {
#pragma unroll
      for (int kk = 0; kk < 4; kk++)
        wgmma_rs_n64(acc, a[kb * 16 + kk * 4], a[kb * 16 + kk * 4 + 1], a[kb * 16 + kk * 4 + 2], a[kb * 16 + kk * 4 + 3], mkd(blo + kk * 128), !(first && kk == 0));
    };
    auto ss64 = [&](float (&acc)[32], int slot, uint32_t blo) {
#pragma unroll
      for (int kk = 0; kk < 4; kk++) wgmma_ss_n64(acc, mkd(xlo - (8 - slot) * (HS >> 4) + kk * 2), mkd(blo + kk * 128), 1);
    };
    auto mma64 = [&](float (&acc)[32], int s, uint32_t blo) { if (s < 8) rs64(acc, s, blo, s == 0); else ss64(acc, 8, blo); };
    const uint32_t qrow = sb + (warp * 16 + (lane & 15)) * 16 + (lane >> 4) * 2048;
    auto qkv_slice = [&](const float (&acc)[32], int i, int s, int ngrp) {
      if (s >= 1 && s <= ngrp) {
        const int t = s - 1, c0 = 8 * i + 2 * t;
        const uint32_t r0 = pack2(acc[8 * t] * rs0, acc[8 * t + 1] * rs0), r1 = pack2(acc[8 * t + 2] * rs1, acc[8 * t + 3] * rs1);
        if (c0 < 26) stsm4(qrow + c0 * 2048, r0, r1, pack2(acc[8 * t + 4] * rs0, acc[8 * t + 5] * rs0), pack2(acc[8 * t + 6] * rs1, acc[8 * t + 7] * rs1));
        else stsm2(qrow + c0 * 2048, r0, r1);
      }
      if (s == ngrp) {
        fence_async_smem();
        __syncwarp();
        if (lane == 0) mbar_arrive(bars + (BAR_QST + i) * 8);
      }
    };
    const float rh0 = 0.5f * rs0, rh1 = 0.5f * rs1;
    auto sig_slice = [&](const float (&acc)[32], int s) {
      if (s >= 1) {
#pragma unroll
        for (int e = 2 * (s - 1); e < 2 * s; e++) {
          const float r = (e & 1) ? rh1 : rh0;
          sg[e] = pack2(fmaf(tanh_hw(acc[2 * e] * r), r, r), fmaf(tanh_hw(acc[2 * e + 1] * r), r, r));
        }
      }
    };
    auto h_val = [&](const float (&acc)[32], int e) { return bmul2(sg[e], pack2(acc[2 * e], acc[2 * e + 1])); };
    auto load_h = [&](int pos) {
#pragma unroll
      for (int kk = (pos & 1) * 2; kk < (pos & 1) * 2 + 2; kk++) {
        const int kb = pos >> 1;
        ldsm4(rowa + kb * HS + (swz ^ (kk << 5)), a[kb * 16 + kk * 4], a[kb * 16 + kk * 4 + 1], a[kb * 16 + kk * 4 + 2], a[kb * 16 + kk * 4 + 3]);
      }
    };

    mbar_wait(bars + BAR_FULL * 8, 0);
    TR(1);
    run_pass<9, 0>(R, false, accB, [&](int s, uint32_t b) { mma64(accA, s, b); }, [&](int s) {
      if (s < 6) centre(s + 2);
      if (s == 6) {
        mbar_wait(bars + BAR_XDONE * 8, 0);
#pragma unroll
        for (int i = 0; i < 16; i++) sg[i] = bsub2(sg[i], (i & 1) ? mp1 : mp0);
#pragma unroll
        for (int kk = 0; kk < 4; kk++) stsm4(rowa + 8 * HS + (swz ^ (kk << 5)), sg[kk * 4], sg[kk * 4 + 1], sg[kk * 4 + 2], sg[kk * 4 + 3]);
        fence_async_smem();
      }
      if (s == 7) asm volatile("bar.sync %0, 128;" ::"r"(1 + wg) : "memory");
    });
    TR(2);
    run_pass<9, 1>(R, false, accA, [&](int s, uint32_t b) { mma64(accB, s, b); }, [&](int s) { qkv_slice(accA, 0, s, 4); });
    TR(3);
    run_pass<9, 2>(R, false, accB, [&](int s, uint32_t b) { mma64(accA, s, b); }, [&](int s) {
      qkv_slice(accB, 1, s, 4);
      if (s == 8) mbar_wait(bars + BAR_W24 * 8, 0);
    });
    TR(4);
    {
      constexpr uint32_t wlo = ((sb + OFF_W24) >> 4) | (8u << 16);
      wg_fence();
#pragma unroll
      for (int k = 0; k < 36; k++) {
        if (k < 32) wgmma_rs_n24(accB, a[k * 4], a[k * 4 + 1], a[k * 4 + 2], a[k * 4 + 3], mkd24(wlo + k * 16), k != 0);
        else wgmma_ss_n24(accB, mkd(xlo + (k - 32) * 2), mkd24(wlo + k * 16), 1);
      }
      wg_commit();
      wg_wait<1>();
      acc_fence(accA);
      if ((threadIdx.x & 127) == 0) mbar_arrive(bars + (BAR_EMPTY + R.prev) * 8);
      R.prev = -1;
#pragma unroll
      for (int s = 1; s <= 4; s++) qkv_slice(accA, 2, s, 4);
    }
    TR(5);
    run_pass<9, 3>(R, false, accB, [&](int s, uint32_t b) { mma64(accA, s, b); }, [&](int s) { qkv_slice(accB, 3, s, 2); });
    TR(6);
    for (int c = 0; c < 8; c++) {
      run_pass<9, 4>(R, false, accA, [&](int s, uint32_t b) { mma64(accB, s, b); }, [&](int s) { sig_slice(accA, s); });
      TR(7 + 2 * c);
      run_pass<9, 5>(R, false, accB, [&](int s, uint32_t b) { mma64(accA, s, b); }, [&](int s) {
        if (s == 1 && (c == 0 || c >= 6)) mbar_wait(bars + (c ? BAR_ATD - 6 + c : BAR_QFREE) * 8, 0);
        if (s >= 1 && s <= 7 && (s & 1)) {
          const int t = s >> 1;
          stsm4(rowa + c * HS + (swz ^ (t << 5)), h_val(accB, 4 * t), h_val(accB, 4 * t + 1), h_val(accB, 4 * t + 2), h_val(accB, 4 * t + 3));
        }
      });
      TR(8 + 2 * c);
    }
    run_pass<9, 6>(R, false, accA, [&](int s, uint32_t b) { mma64(accB, s, b); }, [&](int s) {
      sig_slice(accA, s);
      if (s == 0) {
        fence_async_smem();
        asm volatile("bar.sync %0, 128;" ::"r"(1 + wg) : "memory");
      }
      if (s >= 2) load_h(s - 2);
      if (s == 6) {
        __syncwarp();
        if (lane == 0) mbar_arrive(bars + BAR_OFREE * 8);
      }
    });
    TR(23);
    constexpr uint32_t worlo = ((sb + OFF_WOR) >> 4) | (512u << 16);
    const int grow = m0 + warp * 16;
    int blk = j;
    auto mmaD = [&](float (&acc)[32], int s, uint32_t blo) {
      if (s < 6) rs64(acc, s, blo, s == 0);
      else if (s < 8) ss64(acc, s, blo);
      else if (s == 8) rs64(acc, 6, blo, false);
      else {
        rs64(acc, 7, blo, false);
        wgmma_rs_n64(acc, sg[16], sg[17], 0u, 0u, mkd_sbo0(worlo + blk * 64), 1);
      }
    };
    auto flush_store = [&](const float (&acc)[32], int slot, int t) {
      stsm4(rowa + slot * HS + (swz ^ (t << 5)), pack2(acc[8 * t], acc[8 * t + 1]), pack2(acc[8 * t + 2], acc[8 * t + 3]),
            pack2(acc[8 * t + 4], acc[8 * t + 5]), pack2(acc[8 * t + 6], acc[8 * t + 7]));
    };
    auto flush_issue = [&](int slot, int cb) {
      fence_async_smem();
      __syncwarp();
      if (elect()) { tma2d_red(&mp.out, sb + slot * HS + warp * 2048, cb * 64, grow); bulk_commit(); }
    };
    run_pass<10, 7>(R, false, accB, [&](int s, uint32_t b) { mmaD(accA, s, b); }, [&](int s) {
      if (s < 5) load_h(7 + s);
      if (s >= 1 && s <= 4) {
#pragma unroll
        for (int e = 4 * (s - 1); e < 4 * s; e++) a[96 + e] = h_val(accB, e);
      }
      if (s == 7) {
        mbar_wait(bars + BAR_WOR * 8, 0);
        mbar_wait(bars + BAR_O * 8, 0);
        fence_async_gmem();
        const uint32_t oa = sb + (warp * 16 + (lane & 15)) * 144;
#pragma unroll
        for (int kk = 0; kk < 4; kk++) ldsm4(oa + kk * 32 + (lane >> 4) * 16, a[112 + kk * 4], a[113 + kk * 4], a[114 + kk * 4], a[115 + kk * 4]);
        ldsm2(oa + 128, sg[16], sg[17]);
      }
    });
    TR(24);
    for (int p = 1; p < 9; p += 2) {
      int pb = blk; blk = (blk == 8) ? 0 : blk + 1;
      run_pass<10, 8>(R, false, accA, [&](int s, uint32_t b) { mmaD(accB, s, b); }, [&](int s) {
        const int slot = (p == 5) ? 8 : (p == 7) ? 1 : p + 1;
        if (s >= 1 && s <= 4) flush_store(accA, slot, s - 1);
        if (s == 5) flush_issue(slot, pb);
      });
      TR(24 + p);
      pb = blk; blk = (blk == 8) ? 0 : blk + 1;
      run_pass<10, 9>(R, p == 7, accB, [&](int s, uint32_t b) { mmaD(accA, s, b); }, [&](int s) {
        const int slot = (p < 5) ? p + 2 : p - 5;
        if (s == 0 && p == 7) { asm volatile("cp.async.bulk.wait_group.read 5;" ::: "memory"); __syncwarp(); }
        if (s >= 1 && s <= 4) flush_store(accB, slot, s - 1);
        if (s == 5) flush_issue(slot, pb);
      });
      TR(25 + p);
    }
    wg_wait<0>();
    acc_fence(accA);
    TR(33);
#pragma unroll
    for (int t = 0; t < 4; t++) flush_store(accA, 3, t);
    flush_issue(3, blk);
    bulk_wait_read_all();
    TR(34);
  } else {
    asm volatile("setmaxnreg.dec.sync.aligned.u32 " AREG ";\n");
    if (warp == 8) {
      int st = 0; uint32_t ph = 1;
      auto stage = [&](const CUtensorMap* w, int c0, int c1) {
        mbar_wait(bars + (BAR_EMPTY + st) * 8, ph);
        const uint32_t fb = bars + (BAR_FULL + st) * 8;
        if (elect()) {
          mbar_expect(fb, SLOT);
          tma2d(sb + OFF_RING + st * SLOT, w, c0, c1, fb);
        }
        st++;
        if (st == NSLOT) { st = 0; ph ^= 1; }
      };
      int blk = j;
#pragma unroll 1
      for (int p = 0; p < 30; p++) {
        const CUtensorMap* w; int c0, c1 = 0;
        if (p < 3) { w = &mp.wqkv; c0 = j * 192 + p * 64; }
        else if (p < 21) { w = (p & 1) ? &mp.wg : &mp.wu; c0 = j * 576 + ((p - 3) >> 1) * 64; }
        else { w = &mp.wd; c0 = blk * 64; c1 = j * 576; }
#pragma unroll kPUnroll
        for (int kb = 0; kb < 9; kb++) {
          stage(w, c0, c1 + kb * 64);
        }
        if (p >= 21) {
          stage(&mp.woa, c0, j * 72);
          blk = (blk == 8) ? 0 : blk + 1;
        } else if (p == 3 && elect()) {
          mbar_expect(bars + BAR_WOR * 8, 9 * 1024);
#pragma unroll 1
          for (int b = 0; b < 9; b++) tma2d(sb + OFF_WOR + b * 1024, &mp.wob, b * 64, j * 72 + 64, bars + BAR_WOR * 8);
        }
      }
    } else {
      const int aw = warp - 9;
      if (aw == 2 && elect()) {
        const CUtensorMap* mm = &mp.wg;
#pragma unroll 1
        for (int i = 0; i < 10; i++) asm volatile("prefetch.tensormap [%0];" ::"l"(mm + i) : "memory");
      }
      const unsigned target = (*(volatile unsigned*)&g_epoch + 1) * 8;
      if (aw == 1) {
#pragma unroll 1
        for (int kb = 0; kb < 9; kb++) {
          mbar_wait(bars + (BAR_X + kb) * 8, 0);
          if (elect()) tma2d_store(&mp.out, sb + kb * HS + j * 2048, kb * 64, m0 + j * 16);
        }
        if (elect()) bulk_commit();
        bulk_wait_read_all();
        __syncwarp();
        if (lane == 0) mbar_arrive(bars + BAR_XDONE * 8);
      }
      mbar_wait(bars + (BAR_X + PFW) * 8, 0);
      for (int u = aw * 32 + lane; u < 36 * 4; u += 96) {
        const int r = m * 36 + (u >> 2), c = u & 3;
        asm volatile("prefetch.global.L2 [%0];" ::"l"(reinterpret_cast<const char*>(wqkv) + (size_t)r * (3 * DM * 2) + (c < 3 ? j * 384 + c * 128 : 3072 + j * 48)));
      }
      mbar_wait(bars + BAR_XDONE * 8, 0);
      {
        const char* src = reinterpret_cast<const char*>(wqkv) + 3072 + j * 48;
        const int t = aw * 32 + lane, r = t / 3, ng = t - r * 3;
#pragma unroll 1
        for (int i = 0; i < 18; i++) {
          asm volatile("cp.async.cg.shared.global [%0], [%1], 16;" ::"r"(sb + OFF_W24 + ng * 9216 + (i * 32 + r) * 16),
                       "l"(src + (size_t)(i * 32 + r) * (3 * DM * 2) + ng * 16) : "memory");
          __nanosleep(NAP);
        }
        asm volatile("cp.async.wait_all;" ::: "memory");
        fence_async_smem();
        __syncwarp();
        if (lane == 0) mbar_arrive(bars + BAR_W24 * 8);
        bulk_wait_all();
        asm volatile("bar.sync 3, 96;" ::: "memory");
      }
      auto load_kq = [&](int t) {
        const int r2 = (m0 + t * 48) * 2;
        mbar_expect(bars + BAR_ATI * 8, 9 * (62 + 48) * 16);
        tma2d(sb + OFF_AK, &mp.lkv, r2 - 28, 72 + j * 9, bars + BAR_ATI * 8);
        tma2d(sb + OFF_AQ, &mp.lq, r2, j * 9, bars + BAR_ATI * 8);
      };
      auto load_v = [&](int t) {
        mbar_expect(bars + (BAR_ATI + 1) * 8, 9 * 62 * 16);
        tma2d(sb + OFF_AV, &mp.lkv, (m0 + t * 48) * 2 - 28, 144 + j * 9, bars + (BAR_ATI + 1) * 8);
      };
      if (aw == 0) {
#pragma unroll
        for (int i = 0; i < 4; i++) {
          mbar_wait(bars + (BAR_QST + i) * 8, 0);
          if (elect()) {
            if (i < 3) tma2d_store(&mp.qs8, sb + i * HS, m0 * 2, j * 24 + i * 8);
            else tma2d_store(&mp.qs3, sb + i * HS, m0 * 2, 192 + j * 3);
            bulk_commit();
          }
        }
        bulk_wait_all();
        __syncwarp();
        if (lane == 0) {
          mbar_arrive(bars + BAR_QFREE * 8);
          red_release(&g_cnt[m * 32], 1);
        }
        if (lane < 2) wait_counter(&g_cnt[(lane && m ? m - 1 : m) * 32], target);
        __syncwarp();
        fence_async_gmem();
        if (elect()) { load_kq(0); load_v(0); }
      }
      const int lr = aw * 16 + (lane & 1) + ((lane & 6) << 1), hh = lane >> 3;
      const float sc = 0.23570226039551584f * 1.4426950408889634f;
#pragma unroll 1
      for (int t = 0; t < 3; t++) {
        const bool active = t < 2 || aw < 2;
        const int row = t * 48 + lr;
        float p0[8] = {}, p1[8] = {};
        uint32_t h8 = hh * 8;
        asm volatile("" : "+r"(h8));
        const uint32_t po = (0x70482800u >> h8) & 255, po3 = (0x6C682420u >> h8) & 255;
        mbar_wait(bars + BAR_ATI * 8, t & 1);
        if (active) {
          auto qk = [&](auto nw, uint32_t b) {
            constexpr int N = decltype(nw)::value;
            uint32_t u[N]; float q0[2 * N], q1[2 * N];
            const uint32_t qa = sb + OFF_AQ + lr * 16 + (b >> 4) * 768 + (b & 15), ka = sb + OFF_AK + lr * 16 + (b >> 4) * 992 + (b & 15);
            lds<N>(qa, u);
#pragma unroll
            for (int i = 0; i < N; i++) { q0[2 * i] = bf_lo(u[i]); q0[2 * i + 1] = bf_hi(u[i]); }
            lds<N>(qa + 32, u);
#pragma unroll
            for (int i = 0; i < N; i++) { q1[2 * i] = bf_lo(u[i]); q1[2 * i + 1] = bf_hi(u[i]); }
#pragma unroll
            for (int s = 0; s < 9; s++) {
              lds<N>(ka + (16 - 2 * s) * 16, u);
#pragma unroll
              for (int i = 0; i < N; i++) {
                const float lo = bf_lo(u[i]), hi = bf_hi(u[i]);
                if (s < 8) { p1[s] = fmaf(q1[2 * i], lo, p1[s]); p1[s] = fmaf(q1[2 * i + 1], hi, p1[s]); }
                if (s > 0) { p0[s - 1] = fmaf(q0[2 * i], lo, p0[s - 1]); p0[s - 1] = fmaf(q0[2 * i + 1], hi, p0[s - 1]); }
              }
            }
          };
#pragma unroll kQKU
          for (int i = 0; i < 4; i++) qk(IC<2>(), po + 8 * i);
          qk(IC<1>(), po3);
        }
        asm volatile("bar.sync 3, 96;" ::: "memory");
        if (aw == 0 && elect()) { if (t < 2) load_kq(t + 1); else mbar_arrive(bars + BAR_ATD * 8); }
        if (active) {
          if (m0 + t == 0) {
#pragma unroll
            for (int w = 1; w < 8; w++) { if (row < 2 * w) p0[w] = -INFINITY; if (row + 2 < 2 * w) p1[w] = -INFINITY; }
          }
          auto softmax = [&](float (&p)[8]) {
            const float mx = fmaxf(fmaxf(fmaxf(p[0], p[1]), fmaxf(p[2], p[3])), fmaxf(fmaxf(p[4], p[5]), fmaxf(p[6], p[7])));
            float l = 0.f;
#pragma unroll
            for (int w = 0; w < 8; w++) { p[w] = ex2((p[w] - mx) * sc); l += p[w]; }
            l = __fdividef(1.f, l);
#pragma unroll
            for (int w = 0; w < 8; w++) p[w] *= l;
          };
          softmax(p0); softmax(p1);
        }
        mbar_wait(bars + (BAR_ATI + 1) * 8, t & 1);
        if (active) {
          char* op = reinterpret_cast<char*>(g_o + (blockIdx.x * 128 + row) * 36);
          auto pv = [&](auto nw, uint32_t b) {
            constexpr int N = decltype(nw)::value;
            uint32_t u[N]; float o0[2 * N] = {}, o1[2 * N] = {};
            const uint32_t va = sb + OFF_AV + lr * 16 + (b >> 4) * 992 + (b & 15);
#pragma unroll
            for (int s = 0; s < 9; s++) {
              lds<N>(va + (16 - 2 * s) * 16, u);
#pragma unroll
              for (int i = 0; i < N; i++) {
                const float lo = bf_lo(u[i]), hi = bf_hi(u[i]);
                if (s < 8) { o1[2 * i] = fmaf(p1[s], lo, o1[2 * i]); o1[2 * i + 1] = fmaf(p1[s], hi, o1[2 * i + 1]); }
                if (s > 0) { o0[2 * i] = fmaf(p0[s - 1], lo, o0[2 * i]); o0[2 * i + 1] = fmaf(p0[s - 1], hi, o0[2 * i + 1]); }
              }
            }
            if (N == 2) {
              *reinterpret_cast<uint2*>(op + b) = make_uint2(pack2(o0[0], o0[1]), pack2(o0[2 % (2 * N)], o0[3 % (2 * N)]));
              *reinterpret_cast<uint2*>(op + b + 288) = make_uint2(pack2(o1[0], o1[1]), pack2(o1[2 % (2 * N)], o1[3 % (2 * N)]));
            } else {
              *reinterpret_cast<uint32_t*>(op + b) = pack2(o0[0], o0[1]);
              *reinterpret_cast<uint32_t*>(op + b + 288) = pack2(o1[0], o1[1]);
            }
          };
#pragma unroll kQKU
          for (int i = 0; i < 4; i++) pv(IC<2>(), po + 8 * i);
          pv(IC<1>(), po3);
        }
        asm volatile("bar.sync 3, 96;" ::: "memory");
        if (aw == 0 && elect()) { if (t < 2) load_v(t + 1); else mbar_arrive(bars + (BAR_ATD + 1) * 8); }
      }
      __threadfence();
      asm volatile("bar.sync 3, 96;" ::: "memory");
      if (aw == 0 && lane == 0) {
        mbar_wait(bars + BAR_OFREE * 8, 0);
        fence_async_gmem();
        mbar_expect(bars + BAR_O * 8, OTILE);
        bulk_g2s(sb, g_o + blockIdx.x * 128 * 36, OTILE, bars + BAR_O * 8);
      }
      if (aw == 0 && lane == 0) {
        if (atomicInc(&g_done, 127u) == 127u) atomicAdd(&g_epoch, 1u);
      }
    }
  }
}

typedef CUresult (*EncodeFn)(CUtensorMap*, CUtensorMapDataType, cuuint32_t, void*, const cuuint64_t*, const cuuint64_t*, const cuuint32_t*,
                             const cuuint32_t*, CUtensorMapInterleave, CUtensorMapSwizzle, CUtensorMapL2promotion, CUtensorMapFloatOOBfill);

#define PROMO CU_TENSOR_MAP_L2_PROMOTION_L2_128B
void encode2(EncodeFn fn, CUtensorMap* m, const void* p, uint64_t cols, uint64_t rows, uint32_t bc, uint32_t br, bool raw = false) {
  const cuuint64_t d[2] = {cols, rows}, s[1] = {cols * (raw ? 8 : 2)};
  const cuuint32_t b[2] = {bc, br}, es[2] = {1, 1};
  fn(m, raw ? CU_TENSOR_MAP_DATA_TYPE_UINT64 : CU_TENSOR_MAP_DATA_TYPE_BFLOAT16, 2, const_cast<void*>(p), d, s, b, es, CU_TENSOR_MAP_INTERLEAVE_NONE,
     raw ? CU_TENSOR_MAP_SWIZZLE_NONE : CU_TENSOR_MAP_SWIZZLE_128B, PROMO, CU_TENSOR_MAP_FLOAT_OOB_FILL_NONE);
}

}

extern "C" void kernel_launch(void* const* d_in, const int* in_sizes, int n_in, void* d_out, int out_size) {
  void* fp = nullptr;
  cudaDriverEntryPointQueryResult qr;
  cudaGetDriverEntryPoint("cuTensorMapEncodeTiled", &fp, cudaEnableDefault, &qr);
  EncodeFn fn = (EncodeFn)fp;
  void* qkv = nullptr;
  cudaGetSymbolAddress(&qkv, g_qkv);
  Maps mp;
  encode2(fn, &mp.x, d_in[0], DM, SEQ, 64, NXB == 18 ? 64 : 128);
  encode2(fn, &mp.wqkv, d_in[1], 3 * DM, DM, 64, 64);
  encode2(fn, &mp.wg, d_in[4], FF, DM, 64, 64);
  encode2(fn, &mp.wu, d_in[5], FF, DM, 64, 64);
  encode2(fn, &mp.wd, d_in[6], DM, FF, 64, 64);
  encode2(fn, &mp.woa, d_in[2], DM, DM, 64, 64);
  encode2(fn, &mp.wob, d_in[2], DM, DM, 64, 8);
  encode2(fn, &mp.out, d_out, DM, SEQ, 64, 16);
  encode2(fn, &mp.qs8, qkv, 2 * SEQ, 216, 256, 8, true);
  encode2(fn, &mp.qs3, qkv, 2 * SEQ, 216, 256, 3, true);
  encode2(fn, &mp.lkv, qkv, 2 * SEQ, 216, 124, 9, true);
  encode2(fn, &mp.lq, qkv, 2 * SEQ, 216, 96, 9, true);
  cudaFuncSetAttribute(fused_kernel, cudaFuncAttributeMaxDynamicSharedMemorySize, SMEM_BYTES);
  fused_kernel<<<128, 384, SMEM_BYTES, cudaStreamPerThread>>>(mp, d_in[1]);
}
```

```cpp
#include <cuda_runtime.h>
#include <cuda.h>
#include <cuda_bf16.h>
#include <stdint.h>

namespace {

constexpr int SEQ = 2048, DM = 576, FF = 4608;
constexpr int NSLOT = 9;
constexpr int SLOT = 8192;
constexpr int HS = 16384;
constexpr int OFF_RING = -NSLOT * SLOT;
constexpr int OFF_WOR = 9 * HS;
constexpr int OFF_BAR = OFF_WOR + 9 * 1024;
constexpr int SMEM_BYTES = OFF_BAR - OFF_RING + 512;
constexpr int OFF_W24 = 0;
constexpr int OTILE = 128 * 144;
constexpr int OFF_AK = 6 * HS, OFF_AQ = OFF_AK + 8960, OFF_AV = 7 * HS;
constexpr int BAR_FULL = 0, BAR_EMPTY = 9, BAR_X = 18, BAR_WOR = 36, BAR_XDONE = 37, BAR_W24 = 38, BAR_QST = 39, BAR_WOF = 40, BAR_WOE = 42,
              BAR_ATI = 44, BAR_ATD = 46, BAR_O = 48, BAR_OFREE = 49;
#define RSL 0
#define CAH 1
#define LDH ldsm4_tied
#define XT 256
#define NXB 9
#define NAP 64
#define PFW 4
#define CREG "232"
#define AREG "40"
#define PUNROLL 1
#define QKU 1
constexpr int kQKU = QKU;
constexpr int kPUnroll = PUNROLL;
constexpr int SPIN_LIMIT = 1 << 22;

__device__ uint4 g_qkv[216 * SEQ];
__device__ uint32_t g_o[128 * 128 * 36];
__device__ unsigned g_cnt[16 * 32];
__device__ unsigned g_done;
__device__ unsigned g_epoch;
#define TR(i)
#define TRG(i)
#define TRC(i)

__device__ __forceinline__ uint32_t smem_u32(const void* p) { return (uint32_t)__cvta_generic_to_shared(p); }
__device__ __forceinline__ void wg_fence() { asm volatile("wgmma.fence.sync.aligned;\n" ::: "memory"); }
__device__ __forceinline__ void wg_commit() { asm volatile("wgmma.commit_group.sync.aligned;\n" ::: "memory"); }
template <int N> __device__ __forceinline__ void wg_wait() { asm volatile("wgmma.wait_group.sync.aligned %0;\n" ::"n"(N) : "memory"); }
__device__ __forceinline__ void mbar_init(uint32_t a, int c) { asm volatile("mbarrier.init.shared::cta.b64 [%0], %1;" ::"r"(a), "r"(c) : "memory"); }
__device__ __forceinline__ void mbar_expect(uint32_t a, uint32_t b) { asm volatile("mbarrier.arrive.expect_tx.shared::cta.b64 _, [%0], %1;" ::"r"(a), "r"(b) : "memory"); }
__device__ __forceinline__ void mbar_arrive(uint32_t a) { asm volatile("mbarrier.arrive.shared::cta.b64 _, [%0];" ::"r"(a) : "memory"); }
__device__ __forceinline__ void mbar_wait(uint32_t a, uint32_t par) {
  uint32_t ok; int it = 0;
  while (true) {
    asm volatile("{\n.reg .pred p;\nmbarrier.try_wait.parity.shared::cta.b64 p, [%1], %2;\nselp.u32 %0,1,0,p;\n}\n" : "=r"(ok) : "r"(a), "r"(par) : "memory");
    if (ok) break;
    if (++it > SPIN_LIMIT) __trap();
  }
}
__device__ __forceinline__ uint32_t mbar_try(uint32_t a, uint32_t par) {
  uint32_t ok;
  asm volatile("{\n.reg .pred p;\nmbarrier.try_wait.parity.shared::cta.b64 p, [%1], %2;\nselp.u32 %0,1,0,p;\n}\n" : "=r"(ok) : "r"(a), "r"(par) : "memory");
  return ok;
}
__device__ __forceinline__ void fence_mbar_init() { asm volatile("fence.mbarrier_init.release.cluster;" ::: "memory"); }
__device__ __forceinline__ void fence_async_smem() { asm volatile("fence.proxy.async.shared::cta;\n" ::: "memory"); }
__device__ __forceinline__ void fence_async_gmem() { asm volatile("fence.proxy.async.global;\n" ::: "memory"); }
__device__ __forceinline__ void tma2d(uint32_t dst, const CUtensorMap* m, int c0, int c1, uint32_t bar) {
  asm volatile("cp.async.bulk.tensor.2d.shared::cluster.global.mbarrier::complete_tx::bytes [%0], [%1, {%3, %4}], [%2];" ::"r"(dst), "l"(m), "r"(bar), "r"(c0), "r"(c1) : "memory");
}
__device__ __forceinline__ void bulk_g2s(uint32_t dst, const void* src, uint32_t bytes, uint32_t bar) {
  asm volatile("cp.async.bulk.shared::cluster.global.mbarrier::complete_tx::bytes [%0], [%1], %2, [%3];" ::"r"(dst), "l"(src), "r"(bytes), "r"(bar) : "memory");
}
__device__ __forceinline__ void tma2d_store(const CUtensorMap* m, uint32_t src, int c0, int c1) {
  asm volatile("cp.async.bulk.tensor.2d.global.shared::cta.tile.bulk_group [%0, {%2, %3}], [%1];" ::"l"(m), "r"(src), "r"(c0), "r"(c1) : "memory");
}
__device__ __forceinline__ bool elect() {
  uint32_t p;
  asm volatile("{\n.reg .pred p;\nelect.sync _|p, 0xffffffff;\nselp.u32 %0, 1, 0, p;\n}\n" : "=r"(p));
  return p;
}
__device__ __forceinline__ void tma2d_red(const CUtensorMap* m, uint32_t src, int c0, int c1) {
  asm volatile("cp.reduce.async.bulk.tensor.2d.global.shared::cta.add.tile.bulk_group [%0, {%2, %3}], [%1];" ::"l"(m), "r"(src), "r"(c0), "r"(c1) : "memory");
}
__device__ __forceinline__ void bulk_commit() { asm volatile("cp.async.bulk.commit_group;" ::: "memory"); }
__device__ __forceinline__ void bulk_wait_all() { asm volatile("cp.async.bulk.wait_group 0;" ::: "memory"); }
__device__ __forceinline__ void bulk_wait_read_all() { asm volatile("cp.async.bulk.wait_group.read 0;" ::: "memory"); }
__device__ __forceinline__ void ldsm4(uint32_t addr, uint32_t& r0, uint32_t& r1, uint32_t& r2, uint32_t& r3) {
  asm volatile("ldmatrix.sync.aligned.m8n8.x4.shared.b16 {%0,%1,%2,%3}, [%4];" : "=r"(r0), "=r"(r1), "=r"(r2), "=r"(r3) : "r"(addr) : "memory");
}
__device__ __forceinline__ void ldsm4_tied(uint32_t addr, uint32_t& r0, uint32_t& r1, uint32_t& r2, uint32_t& r3) {
  asm volatile("{\n.reg .pred p;\n.reg .u32 c;\nmov.u32 c, %%nctaid.y;\nsetp.eq.u32 p, c, 1;\n@p ldmatrix.sync.aligned.m8n8.x4.shared.b16 {%0,%1,%2,%3}, [%4];\n}\n"
               : "+r"(r0), "+r"(r1), "+r"(r2), "+r"(r3) : "r"(addr) : "memory");
}
__device__ __forceinline__ void ldsm2(uint32_t addr, uint32_t& r0, uint32_t& r1) {
  asm volatile("ldmatrix.sync.aligned.m8n8.x2.shared.b16 {%0,%1}, [%2];" : "=r"(r0), "=r"(r1) : "r"(addr) : "memory");
}
__device__ __forceinline__ void stsm4(uint32_t addr, uint32_t r0, uint32_t r1, uint32_t r2, uint32_t r3) {
  asm volatile("stmatrix.sync.aligned.m8n8.x4.shared.b16 [%0], {%1,%2,%3,%4};" ::"r"(addr), "r"(r0), "r"(r1), "r"(r2), "r"(r3) : "memory");
}
__device__ __forceinline__ void stsm2(uint32_t addr, uint32_t r0, uint32_t r1) {
  asm volatile("stmatrix.sync.aligned.m8n8.x2.shared.b16 [%0], {%1,%2};" ::"r"(addr), "r"(r0), "r"(r1) : "memory");
}
__device__ __forceinline__ void bulk_prefetch(const void* p, uint32_t bytes) { asm volatile("cp.async.bulk.prefetch.L2.global [%0], %1;" ::"l"(p), "r"(bytes) : "memory"); }
template <int N> __device__ __forceinline__ void lds(uint32_t addr, uint32_t* v) {
  if (N == 4) asm volatile("ld.shared.v4.b32 {%0,%1,%2,%3}, [%4];" : "=r"(v[0]), "=r"(v[1]), "=r"(v[2]), "=r"(v[3]) : "r"(addr));
  else if (N == 2) asm volatile("ld.shared.v2.b32 {%0,%1}, [%2];" : "=r"(v[0]), "=r"(v[1]) : "r"(addr));
  else asm volatile("ld.shared.b32 %0, [%1];" : "=r"(v[0]) : "r"(addr));
}
__device__ __forceinline__ uint32_t pack2(float lo, float hi) { uint32_t r; asm("cvt.rn.bf16x2.f32 %0, %1, %2;" : "=r"(r) : "f"(hi), "f"(lo)); return r; }
__device__ __forceinline__ float bf_lo(uint32_t v) { return __uint_as_float(v << 16); }
__device__ __forceinline__ float bf_hi(uint32_t v) { return __uint_as_float(v & 0xffff0000u); }
__device__ __forceinline__ uint32_t bsub2(uint32_t a, uint32_t b) { uint32_t r; asm("sub.rn.bf16x2 %0, %1, %2;" : "=r"(r) : "r"(a), "r"(b)); return r; }
__device__ __forceinline__ uint32_t bmul2(uint32_t a, uint32_t b) { uint32_t r; asm("mul.rn.bf16x2 %0, %1, %2;" : "=r"(r) : "r"(a), "r"(b)); return r; }
__device__ __forceinline__ float tanh_hw(float x) { float y; asm("tanh.approx.f32 %0, %1;" : "=f"(y) : "f"(x)); return y; }
__device__ __forceinline__ float ex2(float x) { float y; asm("ex2.approx.ftz.f32 %0, %1;" : "=f"(y) : "f"(x)); return y; }
__device__ __forceinline__ unsigned ld_acquire(const unsigned* p) { unsigned v; asm volatile("ld.acquire.gpu.global.u32 %0, [%1];" : "=r"(v) : "l"(p) : "memory"); return v; }
__device__ __forceinline__ void red_release(unsigned* p, unsigned v) { asm volatile("red.release.gpu.global.add.u32 [%0], %1;" ::"l"(p), "r"(v) : "memory"); }
__device__ __forceinline__ void wait_counter(const unsigned* p, unsigned target) {
  int it = 0;
  while ((int)(ld_acquire(p) - target) < 0) { __nanosleep(32); if (++it > SPIN_LIMIT) __trap(); }
}
__device__ __forceinline__ void mma16816(float (&d)[4], uint32_t a0, uint32_t a1, uint32_t a2, uint32_t a3, uint32_t b0, uint32_t b1) {
  asm volatile("mma.sync.aligned.m16n8k16.row.col.f32.bf16.bf16.f32 {%0,%1,%2,%3}, {%4,%5,%6,%7}, {%8,%9}, {%0,%1,%2,%3};"
               : "+f"(d[0]), "+f"(d[1]), "+f"(d[2]), "+f"(d[3]) : "r"(a0), "r"(a1), "r"(a2), "r"(a3), "r"(b0), "r"(b1));
}
__device__ __forceinline__ void mma1688(float (&d)[4], uint32_t a0, uint32_t a1, uint32_t b0) {
  asm volatile("mma.sync.aligned.m16n8k8.row.col.f32.bf16.bf16.f32 {%0,%1,%2,%3}, {%4,%5}, {%6}, {%0,%1,%2,%3};"
               : "+f"(d[0]), "+f"(d[1]), "+f"(d[2]), "+f"(d[3]) : "r"(a0), "r"(a1), "r"(b0));
}

template <int NA> __device__ __forceinline__ void wgmma_rs_n64(float (&d)[NA], uint32_t a0, uint32_t a1, uint32_t a2, uint32_t a3, uint64_t db, int sd) {
  asm volatile("{\n.reg .pred p;\nsetp.ne.b32 p, %37, 0;\n"
    "wgmma.mma_async.sync.aligned.m64n64k16.f32.bf16.bf16 {%0, %1, %2, %3, %4, %5, %6, %7, %8, %9, %10, %11, %12, %13, %14, %15, %16, %17, %18, %19, %20, %21, %22, %23, %24, %25, %26, %27, %28, %29, %30, %31}, {%32, %33, %34, %35}, %36, p, 1, 1, 1;\n"
    "}\n"
    : "+f"(d[0]), "+f"(d[1]), "+f"(d[2]), "+f"(d[3]), "+f"(d[4]), "+f"(d[5]), "+f"(d[6]), "+f"(d[7]), "+f"(d[8]), "+f"(d[9]), "+f"(d[10]), "+f"(d[11]), "+f"(d[12]), "+f"(d[13]), "+f"(d[14]), "+f"(d[15]), "+f"(d[16]), "+f"(d[17]), "+f"(d[18]), "+f"(d[19]), "+f"(d[20]), "+f"(d[21]), "+f"(d[22]), "+f"(d[23]), "+f"(d[24]), "+f"(d[25]), "+f"(d[26]), "+f"(d[27]), "+f"(d[28]), "+f"(d[29]), "+f"(d[30]), "+f"(d[31])
    : "r"(a0), "r"(a1), "r"(a2), "r"(a3), "l"(db), "r"(sd));
}

template <int NA> __device__ __forceinline__ void wgmma_ss_n64(float (&d)[NA], uint64_t da, uint64_t db, int sd) {
  asm volatile("{\n.reg .pred p;\nsetp.ne.b32 p, %34, 0;\n"
    "wgmma.mma_async.sync.aligned.m64n64k16.f32.bf16.bf16 {%0, %1, %2, %3, %4, %5, %6, %7, %8, %9, %10, %11, %12, %13, %14, %15, %16, %17, %18, %19, %20, %21, %22, %23, %24, %25, %26, %27, %28, %29, %30, %31}, %32, %33, p, 1, 1, 0, 1;\n"
    "}\n"
    : "+f"(d[0]), "+f"(d[1]), "+f"(d[2]), "+f"(d[3]), "+f"(d[4]), "+f"(d[5]), "+f"(d[6]), "+f"(d[7]), "+f"(d[8]), "+f"(d[9]), "+f"(d[10]), "+f"(d[11]), "+f"(d[12]), "+f"(d[13]), "+f"(d[14]), "+f"(d[15]), "+f"(d[16]), "+f"(d[17]), "+f"(d[18]), "+f"(d[19]), "+f"(d[20]), "+f"(d[21]), "+f"(d[22]), "+f"(d[23]), "+f"(d[24]), "+f"(d[25]), "+f"(d[26]), "+f"(d[27]), "+f"(d[28]), "+f"(d[29]), "+f"(d[30]), "+f"(d[31])
    : "l"(da), "l"(db), "r"(sd));
}

template <int NA> __device__ __forceinline__ void wgmma_rs_n88(float (&d)[NA], uint32_t a0, uint32_t a1, uint32_t a2, uint32_t a3, uint64_t db, int sd) {
  asm volatile("{\n.reg .pred p;\nsetp.ne.b32 p, %49, 0;\n"
    "wgmma.mma_async.sync.aligned.m64n88k16.f32.bf16.bf16 {%0, %1, %2, %3, %4, %5, %6, %7, %8, %9, %10, %11, %12, %13, %14, %15, %16, %17, %18, %19, %20, %21, %22, %23, %24, %25, %26, %27, %28, %29, %30, %31, %32, %33, %34, %35, %36, %37, %38, %39, %40, %41, %42, %43}, {%44, %45, %46, %47}, %48, p, 1, 1, 1;\n"
    "}\n"
    : "+f"(d[0]), "+f"(d[1]), "+f"(d[2]), "+f"(d[3]), "+f"(d[4]), "+f"(d[5]), "+f"(d[6]), "+f"(d[7]), "+f"(d[8]), "+f"(d[9]), "+f"(d[10]), "+f"(d[11]), "+f"(d[12]), "+f"(d[13]), "+f"(d[14]), "+f"(d[15]), "+f"(d[16]), "+f"(d[17]), "+f"(d[18]), "+f"(d[19]), "+f"(d[20]), "+f"(d[21]), "+f"(d[22]), "+f"(d[23]), "+f"(d[24]), "+f"(d[25]), "+f"(d[26]), "+f"(d[27]), "+f"(d[28]), "+f"(d[29]), "+f"(d[30]), "+f"(d[31]), "+f"(d[32]), "+f"(d[33]), "+f"(d[34]), "+f"(d[35]), "+f"(d[36]), "+f"(d[37]), "+f"(d[38]), "+f"(d[39]), "+f"(d[40]), "+f"(d[41]), "+f"(d[42]), "+f"(d[43])
    : "r"(a0), "r"(a1), "r"(a2), "r"(a3), "l"(db), "r"(sd));
}

template <int NA> __device__ __forceinline__ void wgmma_ss_n88(float (&d)[NA], uint64_t da, uint64_t db, int sd) {
  asm volatile("{\n.reg .pred p;\nsetp.ne.b32 p, %46, 0;\n"
    "wgmma.mma_async.sync.aligned.m64n88k16.f32.bf16.bf16 {%0, %1, %2, %3, %4, %5, %6, %7, %8, %9, %10, %11, %12, %13, %14, %15, %16, %17, %18, %19, %20, %21, %22, %23, %24, %25, %26, %27, %28, %29, %30, %31, %32, %33, %34, %35, %36, %37, %38, %39, %40, %41, %42, %43}, %44, %45, p, 1, 1, 0, 1;\n"
    "}\n"
    : "+f"(d[0]), "+f"(d[1]), "+f"(d[2]), "+f"(d[3]), "+f"(d[4]), "+f"(d[5]), "+f"(d[6]), "+f"(d[7]), "+f"(d[8]), "+f"(d[9]), "+f"(d[10]), "+f"(d[11]), "+f"(d[12]), "+f"(d[13]), "+f"(d[14]), "+f"(d[15]), "+f"(d[16]), "+f"(d[17]), "+f"(d[18]), "+f"(d[19]), "+f"(d[20]), "+f"(d[21]), "+f"(d[22]), "+f"(d[23]), "+f"(d[24]), "+f"(d[25]), "+f"(d[26]), "+f"(d[27]), "+f"(d[28]), "+f"(d[29]), "+f"(d[30]), "+f"(d[31]), "+f"(d[32]), "+f"(d[33]), "+f"(d[34]), "+f"(d[35]), "+f"(d[36]), "+f"(d[37]), "+f"(d[38]), "+f"(d[39]), "+f"(d[40]), "+f"(d[41]), "+f"(d[42]), "+f"(d[43])
    : "l"(da), "l"(db), "r"(sd));
}

__device__ __forceinline__ uint64_t mkd(uint32_t lo) { return ((uint64_t)0x40000040u << 32) | (uint64_t)lo; }
__device__ __forceinline__ uint64_t mkd_sbo0(uint32_t lo) { return ((uint64_t)0x40000000u << 32) | (uint64_t)lo; }

constexpr uint32_t sb = 1024 - OFF_RING;
constexpr uint32_t bars = sb + OFF_BAR;
constexpr uint32_t RING_LO = ((sb + OFF_RING) >> 4) | (512u << 16);

template <int NA> __device__ __forceinline__ void acc_fence(float (&d)[NA]) {
  asm volatile("" : "+f"(d[0]), "+f"(d[1]), "+f"(d[2]), "+f"(d[3]), "+f"(d[4]), "+f"(d[5]), "+f"(d[6]), "+f"(d[7]), "+f"(d[8]), "+f"(d[9]), "+f"(d[10]), "+f"(d[11]), "+f"(d[12]), "+f"(d[13]), "+f"(d[14]), "+f"(d[15]), "+f"(d[16]), "+f"(d[17]), "+f"(d[18]), "+f"(d[19]), "+f"(d[20]), "+f"(d[21]), "+f"(d[22]), "+f"(d[23]), "+f"(d[24]), "+f"(d[25]), "+f"(d[26]), "+f"(d[27]), "+f"(d[28]), "+f"(d[29]), "+f"(d[30]), "+f"(d[31]) :: "memory");
}

template <int V> struct IC { static constexpr int value = V; };

struct Ring {
  int st, prev;
  uint32_t ph;
};

template <int NST, int ID, int NA, class M, class F>
__device__ __forceinline__ void run_pass(Ring& R, bool last, float (&other)[NA], M&& mma, F&& slice) {
#pragma unroll
  for (int s = 0; s < NST; s++) {
    const uint32_t blo = RING_LO + R.st * (SLOT >> 4);
    wg_fence();
    mma(s, blo);
    wg_commit();
    const int cur = R.st;
    R.st++;
    if (R.st == NSLOT) { R.st = 0; R.ph ^= 1; }
    if (!(last && s == NST - 1)) mbar_wait(bars + (BAR_FULL + R.st) * 8, R.ph);
    slice(s);
    wg_wait<1>();
    if (s == 0) acc_fence(other);
    if (R.prev >= 0 && (threadIdx.x & 127) == 0) mbar_arrive(bars + (BAR_EMPTY + R.prev) * 8);
    R.prev = cur;
  }
}

template <int BUF, int PH, bool FIRST, int NA, class M, class F>
__device__ __forceinline__ void run_down(uint32_t wpar, bool last, float (&other)[NA], M&& mma, F&& slice) {
#pragma unroll
  for (int s = 0; s < 10; s++) {
    wg_fence();
    mma(s, s < 9 ? RING_LO + s * (SLOT >> 4) : ((sb + 8 * HS + BUF * SLOT) >> 4) | (512u << 16));
    wg_commit();
    if (s < 8) mbar_wait(bars + (BAR_FULL + s + 1) * 8, PH);
    else if (s == 8) mbar_wait(bars + (BAR_WOF + BUF) * 8, wpar);
    else if (!last) mbar_wait(bars + BAR_FULL * 8, PH ^ 1);
    slice(s);
    wg_wait<1>();
    if (s == 0) acc_fence(other);
    if ((threadIdx.x & 127) == 0) {
      if (s) mbar_arrive(bars + (BAR_EMPTY + s - 1) * 8);
      else {
        if (FIRST) { mbar_arrive(bars + (BAR_EMPTY + 8) * 8); mbar_arrive(bars + (BAR_WOE + BUF) * 8); }
        mbar_arrive(bars + (BAR_WOE + (BUF ^ 1)) * 8);
      }
    }
  }
}

struct Maps {
  CUtensorMap x, wqkv, w24, wg, wu, wd, woa, wob, out, lkv, lq;
};

__global__ void __launch_bounds__(384, 1)
fused_kernel(const __grid_constant__ Maps mp, const void* __restrict__ wqkv, uint32_t zero) {
  extern __shared__ __align__(1024) uint8_t smem[];
  const int j = (blockIdx.x >> 2) & 7, m = (blockIdx.x & 3) + ((blockIdx.x >> 3) & 12);
  const int m0 = m * 128;
  if (threadIdx.x == XT) {
#pragma unroll
    for (int i = 0; i < 9; i++) {
      const uint32_t b = bars + (BAR_X + i) * 8;
      mbar_init(b, 1);
      fence_mbar_init();
      mbar_expect(b, HS);
      tma2d(sb + i * HS, &mp.x, i * 64, m0, b);
    }
  }
  const int warp = __shfl_sync(0xffffffffu, threadIdx.x >> 5, 0), lane = threadIdx.x & 31;

  asm volatile("" ::: "memory");
  if (lane == 0) {
    if (warp == 9) {
      if (smem_u32(smem) != sb + OFF_RING) __trap();
      for (int i = 0; i < NSLOT; i++) { mbar_init(bars + (BAR_FULL + i) * 8, 1); mbar_init(bars + (BAR_EMPTY + i) * 8, 2); }
      fence_mbar_init();
    } else if (warp == 10) {
      mbar_init(bars + BAR_WOR * 8, 1);
      mbar_init(bars + BAR_XDONE * 8, 9);
      mbar_init(bars + BAR_W24 * 8, 1);
      mbar_init(bars + BAR_QST * 8, 8);
      for (int i = 0; i < 2; i++) { mbar_init(bars + (BAR_WOF + i) * 8, 1); mbar_init(bars + (BAR_WOE + i) * 8, 2); }
      for (int i = 0; i < 2; i++) { mbar_init(bars + (BAR_ATI + i) * 8, 1); mbar_init(bars + (BAR_ATD + i) * 8, 1); }
      mbar_init(bars + BAR_O * 8, 1);
      mbar_init(bars + BAR_OFREE * 8, 8);
      fence_mbar_init();
    }
  }
  __syncthreads();

  if (warp < 8) {
    asm volatile("setmaxnreg.inc.sync.aligned.u32 " CREG ";\n");
    const int wg = warp >> 2;
    const int lrow = (warp & 3) * 16 + (lane & 15);
    const uint32_t rowa = sb + wg * 8192 + lrow * 128;
    const uint32_t swz = ((lane >> 4) ^ (lrow & 7)) << 4;
    uint32_t adr[4];
#pragma unroll
    for (int i = 0; i < 4; i++) { adr[i] = rowa + (swz ^ (i << 5)); asm volatile("" : "+r"(adr[i])); }
    uint32_t a[128];
    uint32_t sg[16], oq[4];
    float accA[32], accB[44];
    float rs0, rs1, rh0, rh1;

    Ring R;
    R.st = 0; R.prev = -1; R.ph = 0;
    uint32_t mp0, mp1;
    {
      float cs[2][4] = {}, c1[2][4] = {}, c2[2][4] = {};
      mbar_wait(bars + BAR_X * 8, 0);
      TR(40);
#pragma unroll
      for (int kb = 0; kb <= 9; kb++) {
        uint32_t ok = 1;
        if (kb < 8) ok = mbar_try(bars + (BAR_X + kb + 1) * 8, 0);
        if (kb < 9) {
          if (kb == 8) TR(41);
#pragma unroll
          for (int kk = 0; kk < 4; kk++) {
            uint32_t* r = (kb < 8) ? &a[kb * 16 + kk * 4] : &sg[kk * 4];
            ldsm4(adr[kk] + kb * HS, r[0], r[1], r[2], r[3]);
          }
        }
        if (kb > 0) {
#pragma unroll
          for (int kk = 0; kk < 4; kk++) {
            const uint32_t* r = (kb < 9) ? &a[(kb - 1) * 16 + kk * 4] : &sg[kk * 4];
            mma16816(cs[kk & 1], r[0], r[1], r[2], r[3], 0x3f803f80u, 0x3f803f80u);
            mma1688(c1[0], r[0], r[1], r[0]);
            mma1688(c2[0], r[0], r[1], r[1]);
            mma1688(c1[1], r[2], r[3], r[2]);
            mma1688(c2[1], r[2], r[3], r[3]);
          }
        }
        if (!ok) mbar_wait(bars + (BAR_X + kb + 1) * 8, 0);
      }
      __syncwarp();
      if (lane == 0) mbar_arrive(bars + BAR_XDONE * 8);
      const float mu0 = (cs[0][0] + cs[1][0]) * (1.f / DM), mu1 = (cs[0][2] + cs[1][2]) * (1.f / DM);
      mp0 = pack2(mu0, mu0); mp1 = pack2(mu1, mu1);
      rs0 = (lane & 4) ? c1[0][1] + c1[1][1] : c1[0][0] + c1[1][0];
      rs1 = (lane & 4) ? c2[0][3] + c2[1][3] : c2[0][2] + c2[1][2];
      rh0 = mu0 * mu0; rh1 = mu1 * mu1;
    }
    auto finish_rstd = [&]() {
      const int src = (lane & ~3) | (lane >> 3);
      rs0 = rsqrtf(fmaxf(__shfl_sync(0xffffffffu, rs0, src) * (1.f / DM) - rh0, 0.f) + 1e-5f);
      rs1 = rsqrtf(fmaxf(__shfl_sync(0xffffffffu, rs1, src) * (1.f / DM) - rh1, 0.f) + 1e-5f);
      rh0 = 0.5f * rs0; rh1 = 0.5f * rs1;
    };
    if (RSL < 0) finish_rstd();
    auto centre = [&](int kb) {
#pragma unroll
      for (int i = kb * 16; i < kb * 16 + 16; i++) a[i] = bsub2(a[i], (i & 1) ? mp1 : mp0);
    };
    centre(0);
    if (CAH == 2) centre(1);
    TR(0);

    const uint32_t xlo = ((sb + 8 * HS + wg * 8192) >> 4) | (1u << 16);

    auto rs64 = [&](auto& acc, int kb, uint32_t blo, bool first) {
#pragma unroll
      for (int kk = 0; kk < 4; kk++)
        wgmma_rs_n64(acc, a[kb * 16 + kk * 4], a[kb * 16 + kk * 4 + 1], a[kb * 16 + kk * 4 + 2], a[kb * 16 + kk * 4 + 3], mkd(blo + kk * 128), !(first && kk == 0));
    };
    auto ss64 = [&](auto& acc, int slot, uint32_t blo) {
#pragma unroll
      for (int kk = 0; kk < 4; kk++) wgmma_ss_n64(acc, mkd(xlo - (8 - slot) * (HS >> 4) + kk * 2), mkd(blo + kk * 128), 1);
    };
    auto mma64 = [&](auto& acc, int s, uint32_t blo) { if (s < 8) rs64(acc, s, blo, s == 0); else ss64(acc, 8, blo); };
    char* qp = reinterpret_cast<char*>(g_qkv + (j * 24) * SEQ + m0 + (threadIdx.x >> 5) * 16) + (threadIdx.x & 31) * 4;
    auto qkv_store = [&](const auto& acc, int nb, int chunk) {
      *reinterpret_cast<uint32_t*>(qp + chunk * (SEQ * 16)) = pack2(acc[4 * nb] * rs0, acc[4 * nb + 1] * rs0);
      *reinterpret_cast<uint32_t*>(qp + chunk * (SEQ * 16) + 128) = pack2(acc[4 * nb + 2] * rs1, acc[4 * nb + 3] * rs1);
    };
    auto sig_slice = [&](const auto& acc, int s) {
      if (s >= 1) {
#pragma unroll
        for (int e = 2 * (s - 1); e < 2 * s; e++) {
          const float r = (e & 1) ? rh1 : rh0;
          sg[e] = pack2(fmaf(tanh_hw(acc[2 * e] * r), r, r), fmaf(tanh_hw(acc[2 * e + 1] * r), r, r));
        }
      }
    };
    auto h_val = [&](const auto& acc, int e) { return bmul2(sg[e], pack2(acc[2 * e], acc[2 * e + 1])); };
    auto load_h = [&](int pos) {
#pragma unroll
      for (int kk = (pos & 1) * 2; kk < (pos & 1) * 2 + 2; kk++) {
        const int kb = pos >> 1;
        LDH(adr[kk] + kb * HS, a[kb * 16 + kk * 4], a[kb * 16 + kk * 4 + 1], a[kb * 16 + kk * 4 + 2], a[kb * 16 + kk * 4 + 3]);
      }
    };

    mbar_wait(bars + BAR_FULL * 8, 0);
    TR(1);
    run_pass<9, 0>(R, false, accA, [&](int s, uint32_t b) { mma64(accB, s, b); }, [&](int s) {
      if (s < 8 - CAH) centre(s + CAH);
      if (s == RSL) finish_rstd();
      if (s == 6) {
        mbar_wait(bars + BAR_XDONE * 8, 0);
#pragma unroll
        for (int i = 0; i < 16; i++) sg[i] = bsub2(sg[i], (i & 1) ? mp1 : mp0);
#pragma unroll
        for (int kk = 0; kk < 4; kk++) stsm4(adr[kk] + 8 * HS, sg[kk * 4], sg[kk * 4 + 1], sg[kk * 4 + 2], sg[kk * 4 + 3]);
        fence_async_smem();
      }
      if (s == 7) asm volatile("bar.sync %0, 128;" ::"r"(1 + wg) : "memory");
    });
    TR(2);
    run_pass<9, 1>(R, false, accB, [&](int s, uint32_t b) { mma64(accA, s, b); }, [&](int s) {
      if (s >= 1) qkv_store(accB, s - 1, s - 1);
      if (s == 8) mbar_wait(bars + BAR_W24 * 8, 0);
    });
    TR(3);
    run_pass<9, 2>(R, false, accA, [&](int s, uint32_t b) {
      const uint32_t lo = (b & 0xffffu) | (((OFF_W24 - OFF_RING) >> 4) << 16);
#pragma unroll
      for (int kk = 0; kk < 4; kk++) {
        const int k = s * 4 + kk;
        if (s < 8) wgmma_rs_n88(accB, a[k * 4], a[k * 4 + 1], a[k * 4 + 2], a[k * 4 + 3], mkd(lo + kk * 128), k != 0);
        else wgmma_ss_n88(accB, mkd(xlo + kk * 2), mkd(lo + kk * 128), 1);
      }
    }, [&](int s) { if (s >= 1) qkv_store(accA, s - 1, 7 + s); });
    TR(4);
    TR(5);
    run_pass<9, 3>(R, false, accB, [&](int s, uint32_t b) { mma64(accA, s, b); }, [&](int s) {
      if (s == 1) asm volatile("" : "+f"(accB[32]), "+f"(accB[33]), "+f"(accB[34]), "+f"(accB[35]), "+f"(accB[36]), "+f"(accB[37]), "+f"(accB[38]),
                               "+f"(accB[39]), "+f"(accB[40]), "+f"(accB[41]), "+f"(accB[42]), "+f"(accB[43]) :: "memory");
      if (s >= 1 && s <= 4) { qkv_store(accB, 2 * s - 2, 14 + 2 * s); qkv_store(accB, 2 * s - 1, 15 + 2 * s); }
      if (s == 5) { qp += (192 - 21 * j) * (SEQ * 16); qkv_store(accB, 8, 0); qkv_store(accB, 9, 1); }
      if (s == 6) {
        qkv_store(accB, 10, 2);
        __syncwarp();
        if (lane == 0) mbar_arrive(bars + BAR_QST * 8);
      }
    });
    TR(6);
    for (int c = 0; c < 8; c++) {
      run_pass<9, 4>(R, false, accA, [&](int s, uint32_t b) { mma64(accB, s, b); }, [&](int s) { sig_slice(accA, s); });
      TR(7 + 2 * c);
      run_pass<9, 5>(R, false, accB, [&](int s, uint32_t b) { mma64(accA, s, b); }, [&](int s) {
        if (s == 1 && c >= 6) mbar_wait(bars + (BAR_ATD - 6 + c) * 8, 0);
        if (s >= 1 && s <= 7 && (s & 1)) {
          const int t = s >> 1;
          stsm4(adr[t] + c * HS, h_val(accB, 4 * t), h_val(accB, 4 * t + 1), h_val(accB, 4 * t + 2), h_val(accB, 4 * t + 3));
        }
      });
      TR(8 + 2 * c);
    }
    run_pass<9, 6>(R, false, accA, [&](int s, uint32_t b) { mma64(accB, s, b); }, [&](int s) {
      sig_slice(accA, s);
      if (s == 0) {
        fence_async_smem();
        asm volatile("bar.sync %0, 128;" ::"r"(1 + wg) : "memory");
      }
      if (s >= 2) load_h(s - 2);
      if (s == 6) {
        __syncwarp();
        if (lane == 0) mbar_arrive(bars + BAR_OFREE * 8);
      }
    });
    TR(23);
    constexpr uint32_t worlo = ((sb + OFF_WOR) >> 4) | (512u << 16);
    const int grow = m0 + warp * 16;
    int blk = j;
    auto mmaD = [&](auto& acc, int s, uint32_t blo) {
      if (s < 6) rs64(acc, s, blo, s == 0);
      else if (s < 8) ss64(acc, s, blo);
      else if (s == 8) rs64(acc, 6, blo, false);
      else {
        rs64(acc, 7, blo, false);
        wgmma_rs_n64(acc, oq[0], oq[1], oq[2], oq[3], mkd_sbo0(worlo + blk * 64), 1);
      }
    };
    auto flush_store = [&](const auto& acc, int slot, int t) {
      stsm4(adr[t] + slot * HS, pack2(acc[8 * t], acc[8 * t + 1]), pack2(acc[8 * t + 2], acc[8 * t + 3]),
            pack2(acc[8 * t + 4], acc[8 * t + 5]), pack2(acc[8 * t + 6], acc[8 * t + 7]));
    };
    auto flush_issue = [&](int slot, int cb) {
      fence_async_smem();
      __syncwarp();
      if (elect()) { tma2d_red(&mp.out, sb + slot * HS + warp * 2048, cb * 64, grow); bulk_commit(); }
    };
    run_down<0, 1, true>(0, false, accB, [&](int s, uint32_t b) { mmaD(accA, s, b); }, [&](int s) {
      if (s < 5) load_h(7 + s);
      if (s >= 1 && s <= 4) {
#pragma unroll
        for (int e = 4 * (s - 1); e < 4 * s; e++) a[96 + e] = h_val(accB, e);
      }
      if (s == 7) {
        mbar_wait(bars + BAR_WOR * 8, 0);
        mbar_wait(bars + BAR_O * 8, 0);
        fence_async_gmem();
        const uint32_t oa = sb + ((threadIdx.x >> 5) * 16 + (threadIdx.x & 15)) * 144;
#pragma unroll
        for (int kk = 0; kk < 4; kk++) ldsm4(oa + kk * 32 + (threadIdx.x & 16), a[112 + kk * 4], a[113 + kk * 4], a[114 + kk * 4], a[115 + kk * 4]);
        ldsm2(oa + 128, oq[0], oq[1]);
        asm volatile("mul.lo.u32 %0, %2, %4;\nmul.lo.u32 %1, %3, %4;" : "=r"(oq[2]), "=r"(oq[3]) : "r"(oq[0]), "r"(oq[1]), "r"(zero));
      }
    });
    TR(24);
    auto flush_slice = [&](const auto& acc, int slot, int cb, int s) {
      if (s == 0) { asm volatile("cp.async.bulk.wait_group.read 1;" ::: "memory"); __syncwarp(); }
      if (s >= 1 && s <= 4) flush_store(acc, slot, s - 1);
      if (s == 5) flush_issue(slot, cb);
    };
    for (int p = 1; p < 9; p += 2) {
      int pb = blk; blk = (blk == 8) ? 0 : blk + 1;
      run_down<1, 0, false>((p >> 1) & 1, false, accA, [&](int s, uint32_t b) { mmaD(accB, s, b); }, [&](int s) { flush_slice(accA, 2, pb, s); });
      TR(24 + p);
      pb = blk; blk = (blk == 8) ? 0 : blk + 1;
      run_down<0, 1, false>(((p + 1) >> 1) & 1, p == 7, accB, [&](int s, uint32_t b) { mmaD(accA, s, b); }, [&](int s) { flush_slice(accB, 3, pb, s); });
      TR(25 + p);
    }
    flush_slice(accA, 2, blk, 0);
    wg_wait<0>();
    acc_fence(accA);
    TR(33);
#pragma unroll
    for (int t = 1; t <= 5; t++) flush_slice(accA, 2, blk, t);
    bulk_wait_read_all();
    TR(34);
  } else {
    asm volatile("setmaxnreg.dec.sync.aligned.u32 " AREG ";\n");
    if (warp == 8) {
      int st = 0; uint32_t ph = 1;
      auto stage = [&](const CUtensorMap* w, int c0, int c1) {
        mbar_wait(bars + (BAR_EMPTY + st) * 8, ph);
        const uint32_t fb = bars + (BAR_FULL + st) * 8;
        if (elect()) {
          mbar_expect(fb, SLOT);
          tma2d(sb + OFF_RING + st * SLOT, w, c0, c1, fb);
        }
        st++;
        if (st == NSLOT) { st = 0; ph ^= 1; }
      };
      int blk = j;
#pragma unroll 1
      for (int p = 0; p < 30; p++) {
        const CUtensorMap* w; int c0, c1 = 0;
        if (p < 3) { w = &mp.wqkv; c0 = j * 192 + p * 64; }
        else if (p < 21) { w = (p & 1) ? &mp.wg : &mp.wu; c0 = j * 576 + ((p - 3) >> 1) * 64; }
        else { w = &mp.wd; c0 = blk * 64; c1 = j * 576; }
#pragma unroll kPUnroll
        for (int kb = 0; kb < 9; kb++) {
          stage(w, c0, c1 + kb * 64);
        }
        if (p >= 21) {
          const int q = p - 21;
          mbar_wait(bars + (BAR_WOE + (q & 1)) * 8, (q >> 1) & 1);
          if (elect()) {
            mbar_expect(bars + (BAR_WOF + (q & 1)) * 8, SLOT);
            tma2d(sb + 8 * HS + (q & 1) * SLOT, &mp.woa, c0, j * 72, bars + (BAR_WOF + (q & 1)) * 8);
          }
          blk = (blk == 8) ? 0 : blk + 1;
        }
      }
    } else {
      const int aw = warp - 9;
      if (aw == 2 && elect()) {
        const CUtensorMap* mm = &mp.w24;
#pragma unroll 1
        for (int i = 0; i < 9; i++) asm volatile("prefetch.tensormap [%0];" ::"l"(mm + i) : "memory");
      }
      const unsigned target = (*(volatile unsigned*)&g_epoch + 1) * 8;
      if (aw == 1) {
#pragma unroll 1
        for (int kb = 0; kb < 9; kb++) {
          mbar_wait(bars + (BAR_X + kb) * 8, 0);
          if (elect()) tma2d_store(&mp.out, sb + kb * HS + j * 2048, kb * 64, m0 + j * 16);
        }
        if (elect()) bulk_commit();
        bulk_wait_read_all();
        __syncwarp();
        if (lane == 0) mbar_arrive(bars + BAR_XDONE * 8);
      }
      mbar_wait(bars + (BAR_X + PFW) * 8, 0);
      for (int u = aw * 32 + lane; u < 36 * 4; u += 96) {
        const int r = m * 36 + (u >> 2), c = u & 3;
        asm volatile("prefetch.global.L2 [%0];" ::"l"(reinterpret_cast<const char*>(wqkv) + (size_t)r * (3 * DM * 2) + (c < 3 ? j * 384 + c * 128 : 3072 + j * 48)));
      }
      if (aw == 2) {
        mbar_wait(bars + BAR_XDONE * 8, 0);
        if (elect()) { mbar_expect(bars + BAR_W24 * 8, 9 * 64 * 48); mbar_expect(bars + BAR_WOR * 8, 9 * 1024); }
#pragma unroll 1
        for (int b = 0; b < 18; b++) {
          if (elect()) {
            if (b < 9) tma2d(sb + OFF_W24 + b * SLOT, &mp.w24, 1536 + j * 24, b * 64, bars + BAR_W24 * 8);
            else tma2d(sb + OFF_WOR + (b - 9) * 1024, &mp.wob, (b - 9) * 64, j * 72 + 64, bars + BAR_WOR * 8);
          }
          __nanosleep(NAP);
        }
      }
      if (aw == 1) bulk_wait_all();
      asm volatile("bar.sync 3, 96;" ::: "memory");
      auto load_kq = [&](int t) {
        const int r2 = (m0 + t * 48) * 2;
        mbar_expect(bars + BAR_ATI * 8, 9 * (62 + 48) * 16);
        tma2d(sb + OFF_AK, &mp.lkv, r2 - 28, 72 + j * 9, bars + BAR_ATI * 8);
        tma2d(sb + OFF_AQ, &mp.lq, r2, j * 9, bars + BAR_ATI * 8);
      };
      auto load_v = [&](int t) {
        mbar_expect(bars + (BAR_ATI + 1) * 8, 9 * 62 * 16);
        tma2d(sb + OFF_AV, &mp.lkv, (m0 + t * 48) * 2 - 28, 144 + j * 9, bars + (BAR_ATI + 1) * 8);
      };
      if (aw == 0) {
        mbar_wait(bars + BAR_QST * 8, 0);
        if (lane == 0) {
          red_release(&g_cnt[m * 32], 1);
        }
        if (lane < 2) wait_counter(&g_cnt[(lane && m ? m - 1 : m) * 32], target);
        __syncwarp();
        fence_async_gmem();
        if (elect()) { load_kq(0); load_v(0); }
      }
      uint32_t l16 = (aw * 16 + (lane & 1) + ((lane & 6) << 1)) * 16;
      auto fresh = [&]() { asm volatile("" : "+r"(l16)); return l16; };
      const float sc = 0.23570226039551584f * 1.4426950408889634f;
#pragma unroll 1
      for (int t = 0; t < 3; t++) {
        const bool active = t < 2 || aw < 2;
        float p0[8] = {}, p1[8] = {};
        uint32_t h8 = threadIdx.x & 24;
        asm volatile("" : "+r"(h8));
        const uint32_t po = (0x70482800u >> h8) & 255, po3 = (0x6C682420u >> h8) & 255;
        mbar_wait(bars + BAR_ATI * 8, t & 1);
        if (active) {
          auto qk = [&](auto nw, uint32_t b) {
            constexpr int N = decltype(nw)::value;
            uint32_t u[N]; float q0[2 * N], q1[2 * N];
            const uint32_t o = fresh() + (b & 15), qa = o + (b >> 4) * 768 + (sb + OFF_AQ), ka = o + (b >> 4) * 992 + (sb + OFF_AK);
            lds<N>(qa, u);
#pragma unroll
            for (int i = 0; i < N; i++) { q0[2 * i] = bf_lo(u[i]); q0[2 * i + 1] = bf_hi(u[i]); }
            lds<N>(qa + 32, u);
#pragma unroll
            for (int i = 0; i < N; i++) { q1[2 * i] = bf_lo(u[i]); q1[2 * i + 1] = bf_hi(u[i]); }
#pragma unroll
            for (int s = 0; s < 9; s++) {
              lds<N>(ka + (16 - 2 * s) * 16, u);
#pragma unroll
              for (int i = 0; i < N; i++) {
                const float lo = bf_lo(u[i]), hi = bf_hi(u[i]);
                if (s < 8) { p1[s] = fmaf(q1[2 * i], lo, p1[s]); p1[s] = fmaf(q1[2 * i + 1], hi, p1[s]); }
                if (s > 0) { p0[s - 1] = fmaf(q0[2 * i], lo, p0[s - 1]); p0[s - 1] = fmaf(q0[2 * i + 1], hi, p0[s - 1]); }
              }
            }
          };
#pragma unroll kQKU
          for (int i = 0; i < 4; i++) qk(IC<2>(), po + 8 * i);
          qk(IC<1>(), po3);
        }
        asm volatile("bar.sync 3, 96;" ::: "memory");
        if (aw == 0 && elect()) { if (t < 2) load_kq(t + 1); else mbar_arrive(bars + BAR_ATD * 8); }
        if (active) {
          if (m0 + t == 0) {
            const int row = fresh() >> 4;
#pragma unroll
            for (int w = 1; w < 8; w++) { if (row < 2 * w) p0[w] = -INFINITY; if (row + 2 < 2 * w) p1[w] = -INFINITY; }
          }
          auto softmax = [&](float (&p)[8]) {
            const float mx = fmaxf(fmaxf(fmaxf(p[0], p[1]), fmaxf(p[2], p[3])), fmaxf(fmaxf(p[4], p[5]), fmaxf(p[6], p[7])));
            float l = 0.f;
#pragma unroll
            for (int w = 0; w < 8; w++) { p[w] = ex2((p[w] - mx) * sc); l += p[w]; }
            l = __fdividef(1.f, l);
#pragma unroll
            for (int w = 0; w < 8; w++) p[w] *= l;
          };
          softmax(p0); softmax(p1);
        }
        mbar_wait(bars + (BAR_ATI + 1) * 8, t & 1);
        if (active) {
          char* op = reinterpret_cast<char*>(g_o + (blockIdx.x * 128 + t * 48) * 36) + fresh() * 9;
          auto pv = [&](auto nw, uint32_t b) {
            constexpr int N = decltype(nw)::value;
            uint32_t u[N]; float o0[2 * N] = {}, o1[2 * N] = {};
            const uint32_t va = fresh() + (b & 15) + (b >> 4) * 992 + (sb + OFF_AV);
#pragma unroll
            for (int s = 0; s < 9; s++) {
              lds<N>(va + (16 - 2 * s) * 16, u);
#pragma unroll
              for (int i = 0; i < N; i++) {
                const float lo = bf_lo(u[i]), hi = bf_hi(u[i]);
                if (s < 8) { o1[2 * i] = fmaf(p1[s], lo, o1[2 * i]); o1[2 * i + 1] = fmaf(p1[s], hi, o1[2 * i + 1]); }
                if (s > 0) { o0[2 * i] = fmaf(p0[s - 1], lo, o0[2 * i]); o0[2 * i + 1] = fmaf(p0[s - 1], hi, o0[2 * i + 1]); }
              }
            }
            if (N == 2) {
              *reinterpret_cast<uint2*>(op + b) = make_uint2(pack2(o0[0], o0[1]), pack2(o0[2 % (2 * N)], o0[3 % (2 * N)]));
              *reinterpret_cast<uint2*>(op + b + 288) = make_uint2(pack2(o1[0], o1[1]), pack2(o1[2 % (2 * N)], o1[3 % (2 * N)]));
            } else {
              *reinterpret_cast<uint32_t*>(op + b) = pack2(o0[0], o0[1]);
              *reinterpret_cast<uint32_t*>(op + b + 288) = pack2(o1[0], o1[1]);
            }
          };
#pragma unroll kQKU
          for (int i = 0; i < 4; i++) pv(IC<2>(), po + 8 * i);
          pv(IC<1>(), po3);
        }
        asm volatile("bar.sync 3, 96;" ::: "memory");
        if (aw == 0 && elect()) { if (t < 2) load_v(t + 1); else mbar_arrive(bars + (BAR_ATD + 1) * 8); }
      }
      __threadfence();
      asm volatile("bar.sync 3, 96;" ::: "memory");
      if (aw == 0) {
        mbar_wait(bars + BAR_OFREE * 8, 0);
        fence_async_gmem();
        if (elect()) {
          mbar_expect(bars + BAR_O * 8, OTILE);
          bulk_g2s(sb, g_o + blockIdx.x * 128 * 36, OTILE, bars + BAR_O * 8);
          if (atomicInc(&g_done, 127u) == 127u) atomicAdd(&g_epoch, 1u);
        }
      }
    }
  }
}

typedef CUresult (*EncodeFn)(CUtensorMap*, CUtensorMapDataType, cuuint32_t, void*, const cuuint64_t*, const cuuint64_t*, const cuuint32_t*,
                             const cuuint32_t*, CUtensorMapInterleave, CUtensorMapSwizzle, CUtensorMapL2promotion, CUtensorMapFloatOOBfill);

#define PROMO CU_TENSOR_MAP_L2_PROMOTION_L2_128B
void encode2(EncodeFn fn, CUtensorMap* m, const void* p, uint64_t cols, uint64_t rows, uint32_t bc, uint32_t br, bool raw = false) {
  const cuuint64_t d[2] = {cols, rows}, s[1] = {cols * (raw ? 8 : 2)};
  const cuuint32_t b[2] = {bc, br}, es[2] = {1, 1};
  fn(m, raw ? CU_TENSOR_MAP_DATA_TYPE_UINT64 : CU_TENSOR_MAP_DATA_TYPE_BFLOAT16, 2, const_cast<void*>(p), d, s, b, es, CU_TENSOR_MAP_INTERLEAVE_NONE,
     raw ? CU_TENSOR_MAP_SWIZZLE_NONE : CU_TENSOR_MAP_SWIZZLE_128B, PROMO, CU_TENSOR_MAP_FLOAT_OOB_FILL_NONE);
}

}

extern "C" void kernel_launch(void* const* d_in, const int* in_sizes, int n_in, void* d_out, int out_size) {
  void* fp = nullptr;
  cudaDriverEntryPointQueryResult qr;
  cudaGetDriverEntryPoint("cuTensorMapEncodeTiled", &fp, cudaEnableDefault, &qr);
  EncodeFn fn = (EncodeFn)fp;
  void* qkv = nullptr;
  cudaGetSymbolAddress(&qkv, g_qkv);
  Maps mp;
  encode2(fn, &mp.x, d_in[0], DM, SEQ, 64, NXB == 18 ? 64 : 128);
  encode2(fn, &mp.wqkv, d_in[1], 3 * DM, DM, 64, 64);
  encode2(fn, &mp.w24, d_in[1], 3 * DM, DM, 24, 64);
  encode2(fn, &mp.wg, d_in[4], FF, DM, 64, 64);
  encode2(fn, &mp.wu, d_in[5], FF, DM, 64, 64);
  encode2(fn, &mp.wd, d_in[6], DM, FF, 64, 64);
  encode2(fn, &mp.woa, d_in[2], DM, DM, 64, 64);
  encode2(fn, &mp.wob, d_in[2], DM, DM, 64, 8);
  encode2(fn, &mp.out, d_out, DM, SEQ, 64, 16);
  encode2(fn, &mp.lkv, qkv, 2 * SEQ, 216, 124, 9, true);
  encode2(fn, &mp.lq, qkv, 2 * SEQ, 216, 96, 9, true);
  cudaFuncSetAttribute(fused_kernel, cudaFuncAttributeMaxDynamicSharedMemorySize, SMEM_BYTES);
  fused_kernel<<<128, 384, SMEM_BYTES, cudaStreamPerThread>>>(mp, d_in[1], 0u);
}
```

```cpp
#include <cuda_runtime.h>
#include <cuda.h>
#include <stdint.h>

namespace {

constexpr int SEQ = 2048, DM = 576, FF = 4608;
constexpr int NSLOT = 9;
constexpr int SLOT = 8192;
constexpr int HS = 16384;
constexpr int RING = NSLOT * SLOT;
constexpr int OFF_WOR = 9 * HS;
constexpr int OFF_BAR = OFF_WOR + 4 * 2048;
constexpr int SMEM_BYTES = RING + OFF_BAR + 512;
constexpr int OFF_W24 = 0;
constexpr int OTILE = 128 * 144;
constexpr int OFF_OP = OTILE, OFF_WO0 = OTILE + 2048;
constexpr int OFF_AK = 6 * HS, OFF_AQ = OFF_AK + 8960, OFF_AV = 7 * HS;
constexpr int BAR_FULL = 0, BAR_EMPTY = 9, BAR_X = 18, BAR_WOR = 27, BAR_XDONE = 28, BAR_W24 = 29, BAR_QST = 30, BAR_WOF = 31, BAR_WOE = 33,
              BAR_ATI = 35, BAR_ATD = 37, BAR_O = 39, BAR_OFREE = 40;
constexpr int SPIN_LIMIT = 1 << 22;

__device__ uint4 g_qkv[216 * SEQ];
__device__ uint32_t g_o[128 * 128 * 36];
__device__ unsigned g_cnt[16 * 32];
__device__ unsigned g_done;
__device__ unsigned g_epoch;

__device__ __forceinline__ uint32_t smem_u32(const void* p) { return (uint32_t)__cvta_generic_to_shared(p); }
__device__ __forceinline__ void wg_fence() { asm volatile("wgmma.fence.sync.aligned;\n" ::: "memory"); }
__device__ __forceinline__ void wg_commit() { asm volatile("wgmma.commit_group.sync.aligned;\n" ::: "memory"); }
template <int N> __device__ __forceinline__ void wg_wait() { asm volatile("wgmma.wait_group.sync.aligned %0;\n" ::"n"(N) : "memory"); }
__device__ __forceinline__ void mbar_init(uint32_t a, int c) { asm volatile("mbarrier.init.shared::cta.b64 [%0], %1;" ::"r"(a), "r"(c) : "memory"); }
__device__ __forceinline__ void mbar_expect(uint32_t a, uint32_t b) { asm volatile("mbarrier.arrive.expect_tx.shared::cta.b64 _, [%0], %1;" ::"r"(a), "r"(b) : "memory"); }
__device__ __forceinline__ void mbar_arrive(uint32_t a) { asm volatile("mbarrier.arrive.shared::cta.b64 _, [%0];" ::"r"(a) : "memory"); }
__device__ __forceinline__ uint32_t mbar_try(uint32_t a, uint32_t par) {
  uint32_t ok;
  asm volatile("{\n.reg .pred p;\nmbarrier.try_wait.parity.shared::cta.b64 p, [%1], %2;\nselp.u32 %0,1,0,p;\n}\n" : "=r"(ok) : "r"(a), "r"(par) : "memory");
  return ok;
}
__device__ __forceinline__ void mbar_wait(uint32_t a, uint32_t par) {
  int it = 0;
  while (true) {
    if (mbar_try(a, par)) break;
    if (++it > SPIN_LIMIT) __trap();
  }
}
__device__ __forceinline__ void fence_mbar_init() { asm volatile("fence.mbarrier_init.release.cluster;" ::: "memory"); }
__device__ __forceinline__ void fence_async_smem() { asm volatile("fence.proxy.async.shared::cta;\n" ::: "memory"); }
__device__ __forceinline__ void fence_async_gmem() { asm volatile("fence.proxy.async.global;\n" ::: "memory"); }
__device__ __forceinline__ void tma2d(uint32_t dst, const CUtensorMap* m, int c0, int c1, uint32_t bar) {
  asm volatile("cp.async.bulk.tensor.2d.shared::cluster.global.mbarrier::complete_tx::bytes [%0], [%1, {%3, %4}], [%2];" ::"r"(dst), "l"(m), "r"(bar), "r"(c0), "r"(c1) : "memory");
}
__device__ __forceinline__ void bulk_g2s(uint32_t dst, const void* src, uint32_t bytes, uint32_t bar) {
  asm volatile("cp.async.bulk.shared::cluster.global.mbarrier::complete_tx::bytes [%0], [%1], %2, [%3];" ::"r"(dst), "l"(src), "r"(bytes), "r"(bar) : "memory");
}
__device__ __forceinline__ void tma2d_store(const CUtensorMap* m, uint32_t src, int c0, int c1) {
  asm volatile("cp.async.bulk.tensor.2d.global.shared::cta.tile.bulk_group [%0, {%2, %3}], [%1];" ::"l"(m), "r"(src), "r"(c0), "r"(c1) : "memory");
}
__device__ __forceinline__ bool elect() {
  uint32_t p;
  asm volatile("{\n.reg .pred p;\nelect.sync _|p, 0xffffffff;\nselp.u32 %0, 1, 0, p;\n}\n" : "=r"(p));
  return p;
}
__device__ __forceinline__ void tma2d_red(const CUtensorMap* m, uint32_t src, int c0, int c1) {
  asm volatile("cp.reduce.async.bulk.tensor.2d.global.shared::cta.add.tile.bulk_group [%0, {%2, %3}], [%1];" ::"l"(m), "r"(src), "r"(c0), "r"(c1) : "memory");
}
__device__ __forceinline__ void bulk_commit() { asm volatile("cp.async.bulk.commit_group;" ::: "memory"); }
__device__ __forceinline__ void bulk_wait_all() { asm volatile("cp.async.bulk.wait_group 0;" ::: "memory"); }
__device__ __forceinline__ void bulk_wait_read_all() { asm volatile("cp.async.bulk.wait_group.read 0;" ::: "memory"); }
__device__ __forceinline__ void ldsm4(uint32_t addr, uint32_t& r0, uint32_t& r1, uint32_t& r2, uint32_t& r3) {
  asm volatile("ldmatrix.sync.aligned.m8n8.x4.shared.b16 {%0,%1,%2,%3}, [%4];" : "=r"(r0), "=r"(r1), "=r"(r2), "=r"(r3) : "r"(addr) : "memory");
}
__device__ __forceinline__ void ldsm4_tied(uint32_t zero, uint32_t addr, uint32_t& r0, uint32_t& r1, uint32_t& r2, uint32_t& r3) {
  asm volatile("{\n.reg .pred p;\nsetp.eq.u32 p, %5, 0;\n@p ldmatrix.sync.aligned.m8n8.x4.shared.b16 {%0,%1,%2,%3}, [%4];\n}\n"
               : "+r"(r0), "+r"(r1), "+r"(r2), "+r"(r3) : "r"(addr), "r"(zero) : "memory");
}
__device__ __forceinline__ void stsm4(uint32_t addr, uint32_t r0, uint32_t r1, uint32_t r2, uint32_t r3) {
  asm volatile("stmatrix.sync.aligned.m8n8.x4.shared.b16 [%0], {%1,%2,%3,%4};" ::"r"(addr), "r"(r0), "r"(r1), "r"(r2), "r"(r3) : "memory");
}
template <int N> __device__ __forceinline__ void lds(uint32_t addr, uint32_t* v) {
  if (N == 4) asm volatile("ld.shared.v4.b32 {%0,%1,%2,%3}, [%4];" : "=r"(v[0]), "=r"(v[1]), "=r"(v[2]), "=r"(v[3]) : "r"(addr));
  else if (N == 2) asm volatile("ld.shared.v2.b32 {%0,%1}, [%2];" : "=r"(v[0]), "=r"(v[1]) : "r"(addr));
  else asm volatile("ld.shared.b32 %0, [%1];" : "=r"(v[0]) : "r"(addr));
}
__device__ __forceinline__ uint32_t pack2(float lo, float hi) { uint32_t r; asm("cvt.rn.bf16x2.f32 %0, %1, %2;" : "=r"(r) : "f"(hi), "f"(lo)); return r; }
__device__ __forceinline__ float bf_lo(uint32_t v) { return __uint_as_float(v << 16); }
__device__ __forceinline__ float bf_hi(uint32_t v) { return __uint_as_float(v & 0xffff0000u); }
__device__ __forceinline__ uint32_t bsub2(uint32_t a, uint32_t b) { uint32_t r; asm("sub.rn.bf16x2 %0, %1, %2;" : "=r"(r) : "r"(a), "r"(b)); return r; }
__device__ __forceinline__ uint32_t bmul2(uint32_t a, uint32_t b) { uint32_t r; asm("mul.rn.bf16x2 %0, %1, %2;" : "=r"(r) : "r"(a), "r"(b)); return r; }
__device__ __forceinline__ float tanh_hw(float x) { float y; asm("tanh.approx.f32 %0, %1;" : "=f"(y) : "f"(x)); return y; }
__device__ __forceinline__ float ex2(float x) { float y; asm("ex2.approx.ftz.f32 %0, %1;" : "=f"(y) : "f"(x)); return y; }
__device__ __forceinline__ unsigned ld_acquire(const unsigned* p) { unsigned v; asm volatile("ld.acquire.gpu.global.u32 %0, [%1];" : "=r"(v) : "l"(p) : "memory"); return v; }
__device__ __forceinline__ void red_release(unsigned* p, unsigned v) { asm volatile("red.release.gpu.global.add.u32 [%0], %1;" ::"l"(p), "r"(v) : "memory"); }
__device__ __forceinline__ void wait_counter(const unsigned* p, unsigned target) {
  int it = 0;
  while ((int)(ld_acquire(p) - target) < 0) { __nanosleep(32); if (++it > SPIN_LIMIT) __trap(); }
}
__device__ __forceinline__ void mma16816(float (&d)[4], uint32_t a0, uint32_t a1, uint32_t a2, uint32_t a3, uint32_t b0, uint32_t b1) {
  asm volatile("mma.sync.aligned.m16n8k16.row.col.f32.bf16.bf16.f32 {%0,%1,%2,%3}, {%4,%5,%6,%7}, {%8,%9}, {%0,%1,%2,%3};"
               : "+f"(d[0]), "+f"(d[1]), "+f"(d[2]), "+f"(d[3]) : "r"(a0), "r"(a1), "r"(a2), "r"(a3), "r"(b0), "r"(b1));
}
__device__ __forceinline__ void mma1688(float (&d)[4], uint32_t a0, uint32_t a1, uint32_t b0) {
  asm volatile("mma.sync.aligned.m16n8k8.row.col.f32.bf16.bf16.f32 {%0,%1,%2,%3}, {%4,%5}, {%6}, {%0,%1,%2,%3};"
               : "+f"(d[0]), "+f"(d[1]), "+f"(d[2]), "+f"(d[3]) : "r"(a0), "r"(a1), "r"(b0));
}

template <int NA> __device__ __forceinline__ void wgmma_rs_n64(float (&d)[NA], uint32_t a0, uint32_t a1, uint32_t a2, uint32_t a3, uint64_t db, int sd) {
  asm volatile("{\n.reg .pred p;\nsetp.ne.b32 p, %37, 0;\n"
    "wgmma.mma_async.sync.aligned.m64n64k16.f32.bf16.bf16 {%0, %1, %2, %3, %4, %5, %6, %7, %8, %9, %10, %11, %12, %13, %14, %15, %16, %17, %18, %19, %20, %21, %22, %23, %24, %25, %26, %27, %28, %29, %30, %31}, {%32, %33, %34, %35}, %36, p, 1, 1, 1;\n"
    "}\n"
    : "+f"(d[0]), "+f"(d[1]), "+f"(d[2]), "+f"(d[3]), "+f"(d[4]), "+f"(d[5]), "+f"(d[6]), "+f"(d[7]), "+f"(d[8]), "+f"(d[9]), "+f"(d[10]), "+f"(d[11]), "+f"(d[12]), "+f"(d[13]), "+f"(d[14]), "+f"(d[15]), "+f"(d[16]), "+f"(d[17]), "+f"(d[18]), "+f"(d[19]), "+f"(d[20]), "+f"(d[21]), "+f"(d[22]), "+f"(d[23]), "+f"(d[24]), "+f"(d[25]), "+f"(d[26]), "+f"(d[27]), "+f"(d[28]), "+f"(d[29]), "+f"(d[30]), "+f"(d[31])
    : "r"(a0), "r"(a1), "r"(a2), "r"(a3), "l"(db), "r"(sd));
}

template <int NA> __device__ __forceinline__ void wgmma_ss_n64(float (&d)[NA], uint64_t da, uint64_t db, int sd) {
  asm volatile("{\n.reg .pred p;\nsetp.ne.b32 p, %34, 0;\n"
    "wgmma.mma_async.sync.aligned.m64n64k16.f32.bf16.bf16 {%0, %1, %2, %3, %4, %5, %6, %7, %8, %9, %10, %11, %12, %13, %14, %15, %16, %17, %18, %19, %20, %21, %22, %23, %24, %25, %26, %27, %28, %29, %30, %31}, %32, %33, p, 1, 1, 0, 1;\n"
    "}\n"
    : "+f"(d[0]), "+f"(d[1]), "+f"(d[2]), "+f"(d[3]), "+f"(d[4]), "+f"(d[5]), "+f"(d[6]), "+f"(d[7]), "+f"(d[8]), "+f"(d[9]), "+f"(d[10]), "+f"(d[11]), "+f"(d[12]), "+f"(d[13]), "+f"(d[14]), "+f"(d[15]), "+f"(d[16]), "+f"(d[17]), "+f"(d[18]), "+f"(d[19]), "+f"(d[20]), "+f"(d[21]), "+f"(d[22]), "+f"(d[23]), "+f"(d[24]), "+f"(d[25]), "+f"(d[26]), "+f"(d[27]), "+f"(d[28]), "+f"(d[29]), "+f"(d[30]), "+f"(d[31])
    : "l"(da), "l"(db), "r"(sd));
}

template <int NA> __device__ __forceinline__ void wgmma_rs_n88(float (&d)[NA], uint32_t a0, uint32_t a1, uint32_t a2, uint32_t a3, uint64_t db, int sd) {
  asm volatile("{\n.reg .pred p;\nsetp.ne.b32 p, %49, 0;\n"
    "wgmma.mma_async.sync.aligned.m64n88k16.f32.bf16.bf16 {%0, %1, %2, %3, %4, %5, %6, %7, %8, %9, %10, %11, %12, %13, %14, %15, %16, %17, %18, %19, %20, %21, %22, %23, %24, %25, %26, %27, %28, %29, %30, %31, %32, %33, %34, %35, %36, %37, %38, %39, %40, %41, %42, %43}, {%44, %45, %46, %47}, %48, p, 1, 1, 1;\n"
    "}\n"
    : "+f"(d[0]), "+f"(d[1]), "+f"(d[2]), "+f"(d[3]), "+f"(d[4]), "+f"(d[5]), "+f"(d[6]), "+f"(d[7]), "+f"(d[8]), "+f"(d[9]), "+f"(d[10]), "+f"(d[11]), "+f"(d[12]), "+f"(d[13]), "+f"(d[14]), "+f"(d[15]), "+f"(d[16]), "+f"(d[17]), "+f"(d[18]), "+f"(d[19]), "+f"(d[20]), "+f"(d[21]), "+f"(d[22]), "+f"(d[23]), "+f"(d[24]), "+f"(d[25]), "+f"(d[26]), "+f"(d[27]), "+f"(d[28]), "+f"(d[29]), "+f"(d[30]), "+f"(d[31]), "+f"(d[32]), "+f"(d[33]), "+f"(d[34]), "+f"(d[35]), "+f"(d[36]), "+f"(d[37]), "+f"(d[38]), "+f"(d[39]), "+f"(d[40]), "+f"(d[41]), "+f"(d[42]), "+f"(d[43])
    : "r"(a0), "r"(a1), "r"(a2), "r"(a3), "l"(db), "r"(sd));
}

template <int NA> __device__ __forceinline__ void wgmma_ss_n88(float (&d)[NA], uint64_t da, uint64_t db, int sd) {
  asm volatile("{\n.reg .pred p;\nsetp.ne.b32 p, %46, 0;\n"
    "wgmma.mma_async.sync.aligned.m64n88k16.f32.bf16.bf16 {%0, %1, %2, %3, %4, %5, %6, %7, %8, %9, %10, %11, %12, %13, %14, %15, %16, %17, %18, %19, %20, %21, %22, %23, %24, %25, %26, %27, %28, %29, %30, %31, %32, %33, %34, %35, %36, %37, %38, %39, %40, %41, %42, %43}, %44, %45, p, 1, 1, 0, 1;\n"
    "}\n"
    : "+f"(d[0]), "+f"(d[1]), "+f"(d[2]), "+f"(d[3]), "+f"(d[4]), "+f"(d[5]), "+f"(d[6]), "+f"(d[7]), "+f"(d[8]), "+f"(d[9]), "+f"(d[10]), "+f"(d[11]), "+f"(d[12]), "+f"(d[13]), "+f"(d[14]), "+f"(d[15]), "+f"(d[16]), "+f"(d[17]), "+f"(d[18]), "+f"(d[19]), "+f"(d[20]), "+f"(d[21]), "+f"(d[22]), "+f"(d[23]), "+f"(d[24]), "+f"(d[25]), "+f"(d[26]), "+f"(d[27]), "+f"(d[28]), "+f"(d[29]), "+f"(d[30]), "+f"(d[31]), "+f"(d[32]), "+f"(d[33]), "+f"(d[34]), "+f"(d[35]), "+f"(d[36]), "+f"(d[37]), "+f"(d[38]), "+f"(d[39]), "+f"(d[40]), "+f"(d[41]), "+f"(d[42]), "+f"(d[43])
    : "l"(da), "l"(db), "r"(sd));
}


__device__ __forceinline__ uint64_t mkd(uint32_t lo) { return ((uint64_t)0x40000040u << 32) | (uint64_t)lo; }

constexpr uint32_t sr = 1024, sb = sr + RING;
constexpr uint32_t bars = sb + OFF_BAR;
constexpr uint32_t RING_LO = (sr >> 4) | (512u << 16);

template <int NA> __device__ __forceinline__ void acc_fence(float (&d)[NA]) {
  asm volatile("" : "+f"(d[0]), "+f"(d[1]), "+f"(d[2]), "+f"(d[3]), "+f"(d[4]), "+f"(d[5]), "+f"(d[6]), "+f"(d[7]), "+f"(d[8]), "+f"(d[9]), "+f"(d[10]), "+f"(d[11]), "+f"(d[12]), "+f"(d[13]), "+f"(d[14]), "+f"(d[15]), "+f"(d[16]), "+f"(d[17]), "+f"(d[18]), "+f"(d[19]), "+f"(d[20]), "+f"(d[21]), "+f"(d[22]), "+f"(d[23]), "+f"(d[24]), "+f"(d[25]), "+f"(d[26]), "+f"(d[27]), "+f"(d[28]), "+f"(d[29]), "+f"(d[30]), "+f"(d[31]) :: "memory");
}

template <int V> struct IC { static constexpr int value = V; };

template <int PH, bool FIRST, int NA, class M, class F>
__device__ __forceinline__ void run_pass(float (&other)[NA], M&& mma, F&& slice) {
#pragma unroll
  for (int s = 0; s < 9; s++) {
    wg_fence();
    mma(s, RING_LO + s * (SLOT >> 4));
    wg_commit();
    mbar_wait(bars + (BAR_FULL + (s + 1) % 9) * 8, s < 8 ? PH : PH ^ 1);
    slice(s);
    wg_wait<1>();
    if (s == 0) acc_fence(other);
    if ((s || !FIRST) && (threadIdx.x & 127) == 0) mbar_arrive(bars + (BAR_EMPTY + (s + 8) % 9) * 8);
  }
}

template <int BUF, int PH, bool FIRST, int NA, class M, class F>
__device__ __forceinline__ void run_down(uint32_t wpar, bool last, float (&other)[NA], M&& mma, F&& slice) {
#pragma unroll
  for (int s = 0; s < 10; s++) {
    wg_fence();
    mma(s, s < 9 ? RING_LO + s * (SLOT >> 4) : ((sb + 8 * HS + BUF * SLOT) >> 4) | (512u << 16));
    wg_commit();
    if (s < 8) mbar_wait(bars + (BAR_FULL + s + 1) * 8, PH);
    else if (s == 8) mbar_wait(bars + (BAR_WOF + BUF) * 8, wpar);
    else if (!last) mbar_wait(bars + BAR_FULL * 8, PH ^ 1);
    slice(s);
    wg_wait<1>();
    if (s == 0) acc_fence(other);
    if ((threadIdx.x & 127) == 0) {
      if (s) mbar_arrive(bars + (BAR_EMPTY + s - 1) * 8);
      else {
        if (FIRST) { mbar_arrive(bars + (BAR_EMPTY + 8) * 8); mbar_arrive(bars + (BAR_WOE + BUF) * 8); }
        mbar_arrive(bars + (BAR_WOE + (BUF ^ 1)) * 8);
      }
    }
  }
}

struct Maps {
  CUtensorMap x, wqkv, w24, wg, wu, wd, woa, wob, out, lkv, lq, op;
};

__global__ void __launch_bounds__(384, 1)
fused_kernel(const __grid_constant__ Maps mp, const void* __restrict__ wqkv, uint32_t zero) {
  extern __shared__ __align__(1024) uint8_t smem[];
  const int j = (blockIdx.x >> 2) & 7, m = (blockIdx.x & 3) + ((blockIdx.x >> 3) & 12);
  const int m0 = m * 128;
  if (threadIdx.x == 256) {
#pragma unroll
    for (int i = 0; i < 9; i++) {
      const uint32_t b = bars + (BAR_X + i) * 8;
      mbar_init(b, 1);
      fence_mbar_init();
      mbar_expect(b, HS);
      tma2d(sb + i * HS, &mp.x, i * 64, m0, b);
    }
  }
  const int warp = __shfl_sync(0xffffffffu, threadIdx.x >> 5, 0), lane = threadIdx.x & 31;

  asm volatile("" ::: "memory");
  if (lane == 0) {
    if (warp == 9) {
      if (smem_u32(smem) != sr) __trap();
      for (int i = 0; i < NSLOT; i++) { mbar_init(bars + (BAR_FULL + i) * 8, 1); mbar_init(bars + (BAR_EMPTY + i) * 8, 2); }
      fence_mbar_init();
    } else if (warp == 10) {
      mbar_init(bars + BAR_WOR * 8, 1);
      mbar_init(bars + BAR_XDONE * 8, 9);
      mbar_init(bars + BAR_W24 * 8, 1);
      mbar_init(bars + BAR_QST * 8, 8);
      for (int i = 0; i < 2; i++) { mbar_init(bars + (BAR_WOF + i) * 8, 1); mbar_init(bars + (BAR_WOE + i) * 8, 2); }
      for (int i = 0; i < 2; i++) { mbar_init(bars + (BAR_ATI + i) * 8, 1); mbar_init(bars + (BAR_ATD + i) * 8, 1); }
      mbar_init(bars + BAR_O * 8, 1);
      mbar_init(bars + BAR_OFREE * 8, 8);
      fence_mbar_init();
    }
  }
  __syncthreads();

  if (warp < 8) {
    asm volatile("setmaxnreg.inc.sync.aligned.u32 232;\n");
    const int wg = warp >> 2;
    const int lrow = (warp & 3) * 16 + (lane & 15);
    const uint32_t rowa = sb + wg * 8192 + lrow * 128;
    const uint32_t swz = ((lane >> 4) ^ (lrow & 7)) << 4;
    uint32_t adr[4];
#pragma unroll
    for (int i = 0; i < 4; i++) { adr[i] = rowa + (swz ^ (i << 5)); asm volatile("" : "+r"(adr[i])); }
    uint32_t a[128];
    uint32_t sg[16], oq[4], oz[4];
    float accA[32], accB[44];
    float rs0, rs1, rh0, rh1;
    uint32_t mp0, mp1;
    {
      float cs[2][4] = {}, c1[2][4] = {}, c2[2][4] = {};
      mbar_wait(bars + BAR_X * 8, 0);
#pragma unroll
      for (int kb = 0; kb <= 9; kb++) {
        uint32_t ok = 1;
        if (kb < 8) ok = mbar_try(bars + (BAR_X + kb + 1) * 8, 0);
        if (kb < 9) {
#pragma unroll
          for (int kk = 0; kk < 4; kk++) {
            uint32_t* r = (kb < 8) ? &a[kb * 16 + kk * 4] : &sg[kk * 4];
            ldsm4(adr[kk] + kb * HS, r[0], r[1], r[2], r[3]);
          }
        }
        if (kb > 0) {
#pragma unroll
          for (int kk = 0; kk < 4; kk++) {
            const uint32_t* r = (kb < 9) ? &a[(kb - 1) * 16 + kk * 4] : &sg[kk * 4];
            mma16816(cs[kk & 1], r[0], r[1], r[2], r[3], 0x3f803f80u, 0x3f803f80u);
            mma1688(c1[0], r[0], r[1], r[0]);
            mma1688(c2[0], r[0], r[1], r[1]);
            mma1688(c1[1], r[2], r[3], r[2]);
            mma1688(c2[1], r[2], r[3], r[3]);
          }
        }
        if (!ok) mbar_wait(bars + (BAR_X + kb + 1) * 8, 0);
      }
      __syncwarp();
      if (lane == 0) mbar_arrive(bars + BAR_XDONE * 8);
      const float mu0 = (cs[0][0] + cs[1][0]) * (1.f / DM), mu1 = (cs[0][2] + cs[1][2]) * (1.f / DM);
      mp0 = pack2(mu0, mu0); mp1 = pack2(mu1, mu1);
      rs0 = (lane & 4) ? c1[0][1] + c1[1][1] : c1[0][0] + c1[1][0];
      rs1 = (lane & 4) ? c2[0][3] + c2[1][3] : c2[0][2] + c2[1][2];
      rh0 = mu0 * mu0; rh1 = mu1 * mu1;
    }
    auto finish_rstd = [&]() {
      const int src = (lane & ~3) | (lane >> 3);
      rs0 = rsqrtf(fmaxf(__shfl_sync(0xffffffffu, rs0, src) * (1.f / DM) - rh0, 0.f) + 1e-5f);
      rs1 = rsqrtf(fmaxf(__shfl_sync(0xffffffffu, rs1, src) * (1.f / DM) - rh1, 0.f) + 1e-5f);
      rh0 = 0.5f * rs0; rh1 = 0.5f * rs1;
    };
    auto centre = [&](int kb) {
#pragma unroll
      for (int i = kb * 16; i < kb * 16 + 16; i++) a[i] = bsub2(a[i], (i & 1) ? mp1 : mp0);
    };
    centre(0);

    const uint32_t xlo = ((sb + 8 * HS + wg * 8192) >> 4) | (1u << 16);

    auto rs64 = [&](auto& acc, int kb, uint32_t blo, bool first) {
#pragma unroll
      for (int kk = 0; kk < 4; kk++)
        wgmma_rs_n64(acc, a[kb * 16 + kk * 4], a[kb * 16 + kk * 4 + 1], a[kb * 16 + kk * 4 + 2], a[kb * 16 + kk * 4 + 3], mkd(blo + kk * 128), !(first && kk == 0));
    };
    auto ss64 = [&](auto& acc, int slot, uint32_t blo) {
#pragma unroll
      for (int kk = 0; kk < 4; kk++) wgmma_ss_n64(acc, mkd(xlo - (8 - slot) * (HS >> 4) + kk * 2), mkd(blo + kk * 128), 1);
    };
    auto mma64 = [&](auto& acc, int s, uint32_t blo) { if (s < 8) rs64(acc, s, blo, s == 0); else ss64(acc, 8, blo); };
    char* qp = reinterpret_cast<char*>(g_qkv + (j * 24) * SEQ + m0 + (threadIdx.x >> 5) * 16) + (threadIdx.x & 31) * 4;
    auto qkv_store = [&](const auto& acc, int nb, int chunk) {
      *reinterpret_cast<uint32_t*>(qp + chunk * (SEQ * 16)) = pack2(acc[4 * nb] * rs0, acc[4 * nb + 1] * rs0);
      *reinterpret_cast<uint32_t*>(qp + chunk * (SEQ * 16) + 128) = pack2(acc[4 * nb + 2] * rs1, acc[4 * nb + 3] * rs1);
    };
    auto sig_slice = [&](const auto& acc, int s) {
      if (s >= 1) {
#pragma unroll
        for (int e = 2 * (s - 1); e < 2 * s; e++) {
          const float r = (e & 1) ? rh1 : rh0;
          sg[e] = pack2(fmaf(tanh_hw(acc[2 * e] * r), r, r), fmaf(tanh_hw(acc[2 * e + 1] * r), r, r));
        }
      }
    };
    auto h_val = [&](const auto& acc, int e) { return bmul2(sg[e], pack2(acc[2 * e], acc[2 * e + 1])); };
    auto load_h = [&](int pos) {
#pragma unroll
      for (int kk = (pos & 1) * 2; kk < (pos & 1) * 2 + 2; kk++) {
        const int kb = pos >> 1;
        ldsm4_tied(zero, adr[kk] + kb * HS, a[kb * 16 + kk * 4], a[kb * 16 + kk * 4 + 1], a[kb * 16 + kk * 4 + 2], a[kb * 16 + kk * 4 + 3]);
      }
    };

    mbar_wait(bars + BAR_FULL * 8, 0);
    run_pass<0, true>(accA, [&](int s, uint32_t b) { mma64(accB, s, b); }, [&](int s) {
      if (s < 7) centre(s + 1);
      if (s == 0) finish_rstd();
      if (s == 6) {
        mbar_wait(bars + BAR_XDONE * 8, 0);
#pragma unroll
        for (int i = 0; i < 16; i++) sg[i] = bsub2(sg[i], (i & 1) ? mp1 : mp0);
#pragma unroll
        for (int kk = 0; kk < 4; kk++) stsm4(adr[kk] + 8 * HS, sg[kk * 4], sg[kk * 4 + 1], sg[kk * 4 + 2], sg[kk * 4 + 3]);
        fence_async_smem();
      }
      if (s == 7) asm volatile("bar.sync %0, 128;" ::"r"(1 + wg) : "memory");
    });
    run_pass<1, false>(accB, [&](int s, uint32_t b) { mma64(accA, s, b); }, [&](int s) {
      if (s >= 1) qkv_store(accB, s - 1, s - 1);
      if (s == 8) mbar_wait(bars + BAR_W24 * 8, 0);
    });
    run_pass<0, false>(accA, [&](int s, uint32_t b) {
      const uint32_t lo = (b & 0xffffu) | (((OFF_W24 + RING) >> 4) << 16);
#pragma unroll
      for (int kk = 0; kk < 4; kk++) {
        const int k = s * 4 + kk;
        if (s < 8) wgmma_rs_n88(accB, a[k * 4], a[k * 4 + 1], a[k * 4 + 2], a[k * 4 + 3], mkd(lo + kk * 128), k != 0);
        else wgmma_ss_n88(accB, mkd(xlo + kk * 2), mkd(lo + kk * 128), 1);
      }
    }, [&](int s) { if (s >= 1) qkv_store(accA, s - 1, 7 + s); });
    run_pass<1, false>(accB, [&](int s, uint32_t b) { mma64(accA, s, b); }, [&](int s) {
      if (s == 1) asm volatile("" : "+f"(accB[32]), "+f"(accB[33]), "+f"(accB[34]), "+f"(accB[35]), "+f"(accB[36]), "+f"(accB[37]), "+f"(accB[38]),
                               "+f"(accB[39]), "+f"(accB[40]), "+f"(accB[41]), "+f"(accB[42]), "+f"(accB[43]) :: "memory");
      if (s >= 1 && s <= 4) { qkv_store(accB, 2 * s - 2, 14 + 2 * s); qkv_store(accB, 2 * s - 1, 15 + 2 * s); }
      if (s == 5) { qp += (192 - 21 * j) * (SEQ * 16); qkv_store(accB, 8, 0); qkv_store(accB, 9, 1); }
      if (s == 6) {
        qkv_store(accB, 10, 2);
        __syncwarp();
        if (lane == 0) mbar_arrive(bars + BAR_QST * 8);
      }
    });
    for (int c = 0; c < 8; c++) {
      run_pass<0, false>(accA, [&](int s, uint32_t b) { mma64(accB, s, b); }, [&](int s) { sig_slice(accA, s); });
      run_pass<1, false>(accB, [&](int s, uint32_t b) { mma64(accA, s, b); }, [&](int s) {
        if (s == 1 && c >= 6) mbar_wait(bars + (BAR_ATD - 6 + c) * 8, 0);
        if (s >= 1 && s <= 7 && (s & 1)) {
          const int t = s >> 1;
          stsm4(adr[t] + c * HS, h_val(accB, 4 * t), h_val(accB, 4 * t + 1), h_val(accB, 4 * t + 2), h_val(accB, 4 * t + 3));
        }
      });
    }
    run_pass<0, false>(accA, [&](int s, uint32_t b) { mma64(accB, s, b); }, [&](int s) {
      sig_slice(accA, s);
      if (s == 0) {
        fence_async_smem();
        asm volatile("bar.sync %0, 128;" ::"r"(1 + wg) : "memory");
      }
      if (s >= 2) load_h(s - 2);
      if (s == 6) {
        __syncwarp();
        if (lane == 0) mbar_arrive(bars + BAR_OFREE * 8);
      }
    });
    constexpr uint32_t worlo = ((sb + OFF_WOR) >> 4) | (512u << 16);
    const int grow = m0 + warp * 16;
    int blk = j;
    auto mmaD = [&](auto& acc, int s, uint32_t blo, const uint32_t* sh, uint32_t shlo) {
      if (s < 6) rs64(acc, s, blo, s == 0);
      else if (s < 8) ss64(acc, s, blo);
      else rs64(acc, s - 2, blo, false);
      if (s == 9 && sh) wgmma_rs_n64(acc, sh[0], sh[1], sh[2], sh[3], mkd(shlo), 1);
    };
    auto flush_store = [&](const auto& acc, int slot, int t) {
      stsm4(adr[t] + slot * HS, pack2(acc[8 * t], acc[8 * t + 1]), pack2(acc[8 * t + 2], acc[8 * t + 3]),
            pack2(acc[8 * t + 4], acc[8 * t + 5]), pack2(acc[8 * t + 6], acc[8 * t + 7]));
    };
    auto flush_issue = [&](int slot, int cb) {
      fence_async_smem();
      __syncwarp();
      if (elect()) { tma2d_red(&mp.out, sb + slot * HS + warp * 2048, cb * 64, grow); bulk_commit(); }
    };
    run_down<0, 1, true>(0, false, accB, [&](int s, uint32_t b) { mmaD(accA, s, b, oz, ((sb + OFF_WO0) >> 4) | (512u << 16)); }, [&](int s) {
      if (s < 5) load_h(7 + s);
      if (s >= 1 && s <= 4) {
#pragma unroll
        for (int e = 4 * (s - 1); e < 4 * s; e++) a[96 + e] = h_val(accB, e);
      }
      if (s == 7) {
        mbar_wait(bars + BAR_WOR * 8, 0);
        mbar_wait(bars + BAR_O * 8, 0);
        fence_async_gmem();
        const uint32_t orow = (threadIdx.x >> 5) * 16 + (threadIdx.x & 15), oa = sb + orow * 144, odd = j & 1;
#pragma unroll
        for (int kk = 0; kk < 4; kk++) ldsm4(oa + odd * 16 + kk * 32 + (threadIdx.x & 16), a[112 + kk * 4], a[113 + kk * 4], a[114 + kk * 4], a[115 + kk * 4]);
        ldsm4(((threadIdx.x >> 4) & 1) == odd ? oa + 128 - odd * 128 : sb + OFF_OP + orow * 16, oq[0], oq[1], oq[2], oq[3]);
#pragma unroll
        for (int i = 0; i < 4; i++) asm volatile("mul.lo.u32 %0, %1, %2;" : "=r"(oz[i]) : "r"(oq[i]), "r"(odd ^ 1));
      }
    });
    auto flush_slice = [&](const auto& acc, int slot, int cb, int s) {
      if (s == 0) { asm volatile("cp.async.bulk.wait_group.read 1;" ::: "memory"); __syncwarp(); }
      if (s >= 1 && s <= 4) flush_store(acc, slot, s - 1);
      if (s == 5) flush_issue(slot, cb);
    };
    for (int p = 1; p < 9; p += 2) {
      int pb = blk; blk = (blk == 8) ? 0 : blk + 1;
      run_down<1, 0, false>((p >> 1) & 1, false, accA, [&](int s, uint32_t b) { mmaD(accB, s, b, oq, worlo + (p >> 1) * 128); }, [&](int s) { flush_slice(accA, 2, pb, s); });
      pb = blk; blk = (blk == 8) ? 0 : blk + 1;
      if (p == 7 && wg == 1) asm volatile("bar.sync 5, 256;" ::: "memory");
      run_down<0, 1, false>(((p + 1) >> 1) & 1, p == 7, accB, [&](int s, uint32_t b) { mmaD(accA, s, b, nullptr, 0); }, [&](int s) {
        flush_slice(accB, 3, pb, s);
        if (s == 3 && p == 7 && wg == 0) asm volatile("bar.arrive 5, 256;" ::: "memory");
      });
    }
    flush_slice(accA, 2, blk, 0);
    wg_wait<0>();
    acc_fence(accA);
#pragma unroll
    for (int t = 1; t <= 5; t++) flush_slice(accA, 2, blk, t);
    bulk_wait_read_all();
  } else {
    asm volatile("setmaxnreg.dec.sync.aligned.u32 40;\n");
    if (warp == 8) {
      int st = 0; uint32_t ph = 1;
      auto stage = [&](const CUtensorMap* w, int c0, int c1) {
        mbar_wait(bars + (BAR_EMPTY + st) * 8, ph);
        const uint32_t fb = bars + (BAR_FULL + st) * 8;
        if (elect()) {
          mbar_expect(fb, SLOT);
          tma2d(sr + st * SLOT, w, c0, c1, fb);
        }
        st++;
        if (st == NSLOT) { st = 0; ph ^= 1; }
      };
      int blk = j;
#pragma unroll 1
      for (int p = 0; p < 30; p++) {
        const CUtensorMap* w; int c0, c1 = 0;
        if (p < 3) { w = &mp.wqkv; c0 = j * 192 + p * 64; }
        else if (p < 21) { w = (p & 1) ? &mp.wg : &mp.wu; c0 = j * 576 + ((p - 3) >> 1) * 64; }
        else { w = &mp.wd; c0 = blk * 64; c1 = j * 576; }
#pragma unroll 1
        for (int kb = 0; kb < 9; kb++) {
          stage(w, c0, c1 + kb * 64);
        }
        if (p >= 21) {
          const int q = p - 21;
          mbar_wait(bars + (BAR_WOE + (q & 1)) * 8, (q >> 1) & 1);
          if (elect()) {
            mbar_expect(bars + (BAR_WOF + (q & 1)) * 8, SLOT);
            tma2d(sb + 8 * HS + (q & 1) * SLOT, &mp.woa, c0, j * 72 + (j & 1) * 8, bars + (BAR_WOF + (q & 1)) * 8);
          }
          blk = (blk == 8) ? 0 : blk + 1;
        }
      }
    } else {
      const int aw = warp - 9;
      if (aw == 2 && elect()) {
        const CUtensorMap* mm = &mp.w24;
#pragma unroll 1
        for (int i = 0; i < 10; i++) asm volatile("prefetch.tensormap [%0];" ::"l"(mm + i) : "memory");
      }
      const unsigned target = (*(volatile unsigned*)&g_epoch + 1) * 8;
      if (aw == 1) {
#pragma unroll 1
        for (int kb = 0; kb < 9; kb++) {
          mbar_wait(bars + (BAR_X + kb) * 8, 0);
          if (elect()) tma2d_store(&mp.out, sb + kb * HS + j * 2048, kb * 64, m0 + j * 16);
        }
        if (elect()) bulk_commit();
        bulk_wait_read_all();
        __syncwarp();
        if (lane == 0) mbar_arrive(bars + BAR_XDONE * 8);
      }
      mbar_wait(bars + (BAR_X + 4) * 8, 0);
      for (int u = aw * 32 + lane; u < 36 * 4; u += 96) {
        const int r = m * 36 + (u >> 2), c = u & 3;
        asm volatile("prefetch.global.L2 [%0];" ::"l"(reinterpret_cast<const char*>(wqkv) + (size_t)r * (3 * DM * 2) + (c < 3 ? j * 384 + c * 128 : 3072 + j * 48)));
      }
      if (aw == 2) {
        mbar_wait(bars + BAR_XDONE * 8, 0);
        if (elect()) { mbar_expect(bars + BAR_W24 * 8, 9 * 64 * 48); mbar_expect(bars + BAR_WOR * 8, 4 * 2048); }
#pragma unroll 1
        for (int b = 0; b < 13; b++) {
          if (elect()) {
            if (b < 9) tma2d(sb + OFF_W24 + b * SLOT, &mp.w24, 1536 + j * 24, b * 64, bars + BAR_W24 * 8);
            else tma2d(sb + OFF_WOR + (b - 9) * 2048, &mp.wob, ((j + 2 * b - 17) % 9) * 64, (j & ~1) * 72 + 64, bars + BAR_WOR * 8);
          }
          __nanosleep(64);
        }
      }
      if (aw == 1) bulk_wait_all();
      asm volatile("bar.sync 3, 96;" ::: "memory");
      auto load_kq = [&](int t) {
        const int r2 = (m0 + t * 48) * 2;
        mbar_expect(bars + BAR_ATI * 8, 9 * (62 + 50) * 16);
        tma2d(sb + OFF_AK, &mp.lkv, r2 - 28, 72 + j * 9, bars + BAR_ATI * 8);
        tma2d(sb + OFF_AQ, &mp.lq, r2, j * 9, bars + BAR_ATI * 8);
      };
      auto load_v = [&](int t) {
        mbar_expect(bars + (BAR_ATI + 1) * 8, 9 * 62 * 16);
        tma2d(sb + OFF_AV, &mp.lkv, (m0 + t * 48) * 2 - 28, 144 + j * 9, bars + (BAR_ATI + 1) * 8);
      };
      if (aw == 0) {
        mbar_wait(bars + BAR_QST * 8, 0);
        if (lane == 0) {
          red_release(&g_cnt[m * 32], 1);
        }
        if (lane < 2) wait_counter(&g_cnt[(lane && m ? m - 1 : m) * 32], target);
        __syncwarp();
        fence_async_gmem();
        if (elect()) { load_kq(0); load_v(0); }
      }
      uint32_t l16 = (aw * 16 + (lane & 1) + (lane & 2) * 2 + (lane >> 4) * 8) * 16;
      auto fresh = [&]() { asm volatile("" : "+r"(l16)); return l16; };
      const float sc = 0.23570226039551584f * 1.4426950408889634f;
#pragma unroll 1
      for (int t = 0; t < 3; t++) {
        const bool active = t < 2 || aw < 2;
        float p0[8] = {}, p1[8] = {};
        uint32_t h8 = (threadIdx.x & 12) * 2;
        asm volatile("" : "+r"(h8));
        const uint32_t po = (0x70482800u >> h8) & 255, po3 = (0x6C682420u >> h8) & 255;
        const uint32_t px = (0x00100000u >> h8) & 255;
        mbar_wait(bars + BAR_ATI * 8, t & 1);
        if (active) {
          auto qk = [&](auto nw, uint32_t b) {
            constexpr int N = decltype(nw)::value;
            uint32_t u[N]; float q0[2 * N], q1[2 * N];
            const uint32_t o = fresh() + (b & 15), qa = o + (b >> 4) * 800 + (sb + OFF_AQ), ka = o + (b >> 4) * 992 + (sb + OFF_AK);
            lds<N>(qa, u);
#pragma unroll
            for (int i = 0; i < N; i++) { q0[2 * i] = bf_lo(u[i]); q0[2 * i + 1] = bf_hi(u[i]); }
            lds<N>(qa + 32, u);
#pragma unroll
            for (int i = 0; i < N; i++) { q1[2 * i] = bf_lo(u[i]); q1[2 * i + 1] = bf_hi(u[i]); }
#pragma unroll
            for (int s = 0; s < 9; s++) {
              lds<N>(ka + (16 - 2 * s) * 16, u);
#pragma unroll
              for (int i = 0; i < N; i++) {
                const float lo = bf_lo(u[i]), hi = bf_hi(u[i]);
                if (s < 8) { p1[s] = fmaf(q1[2 * i], lo, p1[s]); p1[s] = fmaf(q1[2 * i + 1], hi, p1[s]); }
                if (s > 0) { p0[s - 1] = fmaf(q0[2 * i], lo, p0[s - 1]); p0[s - 1] = fmaf(q0[2 * i + 1], hi, p0[s - 1]); }
              }
            }
          };
#pragma unroll 1
          for (int i = 0; i < 4; i++) qk(IC<2>(), po + ((8 * i) ^ px));
          qk(IC<1>(), po3);
        }
        asm volatile("bar.sync 3, 96;" ::: "memory");
        if (aw == 0 && elect()) { if (t < 2) load_kq(t + 1); else mbar_arrive(bars + BAR_ATD * 8); }
        if (active) {
          if (m0 + t == 0) {
            const int row = fresh() >> 4;
#pragma unroll
            for (int w = 1; w < 8; w++) { if (row < 2 * w) p0[w] = -INFINITY; if (row + 2 < 2 * w) p1[w] = -INFINITY; }
          }
          auto softmax = [&](float (&p)[8]) {
            const float mx = fmaxf(fmaxf(fmaxf(p[0], p[1]), fmaxf(p[2], p[3])), fmaxf(fmaxf(p[4], p[5]), fmaxf(p[6], p[7])));
            const float ms = -mx * sc;
            float l = 0.f;
#pragma unroll
            for (int w = 0; w < 8; w++) { p[w] = ex2(fmaf(p[w], sc, ms)); l += p[w]; }
            l = __fdividef(1.f, l);
#pragma unroll
            for (int w = 0; w < 8; w++) p[w] *= l;
          };
          softmax(p0); softmax(p1);
        }
        mbar_wait(bars + (BAR_ATI + 1) * 8, t & 1);
        if (active) {
          char* op = reinterpret_cast<char*>(g_o + (blockIdx.x * 128 + t * 48) * 36) + fresh() * 9;
          auto pv = [&](auto nw, uint32_t b) {
            constexpr int N = decltype(nw)::value;
            uint32_t u[N]; float o0[2 * N] = {}, o1[2 * N] = {};
            const uint32_t va = fresh() + (b & 15) + (b >> 4) * 992 + (sb + OFF_AV);
#pragma unroll
            for (int s = 0; s < 9; s++) {
              lds<N>(va + (16 - 2 * s) * 16, u);
#pragma unroll
              for (int i = 0; i < N; i++) {
                const float lo = bf_lo(u[i]), hi = bf_hi(u[i]);
                if (s < 8) { o1[2 * i] = fmaf(p1[s], lo, o1[2 * i]); o1[2 * i + 1] = fmaf(p1[s], hi, o1[2 * i + 1]); }
                if (s > 0) { o0[2 * i] = fmaf(p0[s - 1], lo, o0[2 * i]); o0[2 * i + 1] = fmaf(p0[s - 1], hi, o0[2 * i + 1]); }
              }
            }
            if (N == 2) {
              *reinterpret_cast<uint2*>(op + b) = make_uint2(pack2(o0[0], o0[1]), pack2(o0[2 % (2 * N)], o0[3 % (2 * N)]));
              *reinterpret_cast<uint2*>(op + b + 288) = make_uint2(pack2(o1[0], o1[1]), pack2(o1[2 % (2 * N)], o1[3 % (2 * N)]));
            } else {
              *reinterpret_cast<uint32_t*>(op + b) = pack2(o0[0], o0[1]);
              *reinterpret_cast<uint32_t*>(op + b + 288) = pack2(o1[0], o1[1]);
            }
          };
#pragma unroll 1
          for (int i = 0; i < 4; i++) pv(IC<2>(), po + ((8 * i) ^ px));
          pv(IC<1>(), po3);
        }
        asm volatile("bar.sync 3, 96;" ::: "memory");
        if (aw == 0 && elect()) { if (t < 2) load_v(t + 1); else mbar_arrive(bars + (BAR_ATD + 1) * 8); }
      }
      if (aw == 0) {
        if (elect()) {
          red_release(&g_cnt[m * 32 + 8 + (j >> 1)], 1);
          wait_counter(&g_cnt[m * 32 + 8 + (j >> 1)], (*(volatile unsigned*)&g_epoch + 1) * 2);
        }
        __syncwarp();
        mbar_wait(bars + BAR_OFREE * 8, 0);
        fence_async_gmem();
        if (elect()) {
          mbar_expect(bars + BAR_O * 8, OTILE + 4096);
          bulk_g2s(sb, g_o + blockIdx.x * 128 * 36, OTILE, bars + BAR_O * 8);
          tma2d(sb + OFF_OP, &mp.op, (j & 1) * 16, (blockIdx.x ^ 4) * 128, bars + BAR_O * 8);
          tma2d(sb + OFF_WO0, &mp.wob, j * 64, (j & ~1) * 72 + 64, bars + BAR_O * 8);
          if (atomicInc(&g_done, 127u) == 127u) atomicAdd(&g_epoch, 1u);
        }
      }
    }
  }
}

typedef CUresult (*EncodeFn)(CUtensorMap*, CUtensorMapDataType, cuuint32_t, void*, const cuuint64_t*, const cuuint64_t*, const cuuint32_t*,
                             const cuuint32_t*, CUtensorMapInterleave, CUtensorMapSwizzle, CUtensorMapL2promotion, CUtensorMapFloatOOBfill);

void encode2(EncodeFn fn, CUtensorMap* m, const void* p, uint64_t cols, uint64_t rows, uint32_t bc, uint32_t br, bool raw = false) {
  const cuuint64_t d[2] = {cols, rows}, s[1] = {cols * (raw ? 8 : 2)};
  const cuuint32_t b[2] = {bc, br}, es[2] = {1, 1};
  fn(m, raw ? CU_TENSOR_MAP_DATA_TYPE_UINT64 : CU_TENSOR_MAP_DATA_TYPE_BFLOAT16, 2, const_cast<void*>(p), d, s, b, es, CU_TENSOR_MAP_INTERLEAVE_NONE,
     raw ? CU_TENSOR_MAP_SWIZZLE_NONE : CU_TENSOR_MAP_SWIZZLE_128B, CU_TENSOR_MAP_L2_PROMOTION_L2_128B, CU_TENSOR_MAP_FLOAT_OOB_FILL_NONE);
}

}

extern "C" void kernel_launch(void* const* d_in, const int* in_sizes, int n_in, void* d_out, int out_size) {
  void* fp = nullptr;
  cudaDriverEntryPointQueryResult qr;
  cudaGetDriverEntryPoint("cuTensorMapEncodeTiled", &fp, cudaEnableDefault, &qr);
  EncodeFn fn = (EncodeFn)fp;
  void* qkv = nullptr;
  cudaGetSymbolAddress(&qkv, g_qkv);
  Maps mp;
  encode2(fn, &mp.x, d_in[0], DM, SEQ, 64, 128);
  encode2(fn, &mp.wqkv, d_in[1], 3 * DM, DM, 64, 64);
  encode2(fn, &mp.w24, d_in[1], 3 * DM, DM, 24, 64);
  encode2(fn, &mp.wg, d_in[4], FF, DM, 64, 64);
  encode2(fn, &mp.wu, d_in[5], FF, DM, 64, 64);
  encode2(fn, &mp.wd, d_in[6], DM, FF, 64, 64);
  encode2(fn, &mp.woa, d_in[2], DM, DM, 64, 64);
  encode2(fn, &mp.wob, d_in[2], DM, DM, 64, 16);
  encode2(fn, &mp.out, d_out, DM, SEQ, 64, 16);
  encode2(fn, &mp.lkv, qkv, 2 * SEQ, 216, 124, 9, true);
  void* op = nullptr;
  cudaGetSymbolAddress(&op, g_o);
  encode2(fn, &mp.op, op, 18, 128 * 128, 2, 128, true);
  encode2(fn, &mp.lq, qkv, 2 * SEQ, 216, 100, 9, true);
  cudaFuncSetAttribute(fused_kernel, cudaFuncAttributeMaxDynamicSharedMemorySize, SMEM_BYTES);
  fused_kernel<<<128, 384, SMEM_BYTES, cudaStreamPerThread>>>(mp, d_in[1], 0u);
}
```

```cpp
#include <cuda_runtime.h>
#include <cuda.h>
#include <stdint.h>

namespace {

constexpr int SEQ = 2048, DM = 576, FF = 4608;
constexpr int NSLOT = 9;
constexpr int SLOT = 8192;
constexpr int HS = 16384;
constexpr int RING = NSLOT * SLOT;
constexpr int OFF_WOR = 9 * HS;
constexpr int OFF_BAR = OFF_WOR + 4 * 2048;
constexpr int SMEM_BYTES = RING + OFF_BAR + 512;
constexpr int OFF_W24 = 0;
constexpr int OTILE = 128 * 144;
constexpr int OFF_OP = OTILE, OFF_WO0 = OTILE + 2048;
constexpr int OFF_AK = 6 * HS, OFF_AQ = OFF_AK + 8960, OFF_AV = 7 * HS;
constexpr int BAR_FULL = 0, BAR_EMPTY = 9, BAR_X = 18, BAR_WOR = 27, BAR_XDONE = 28, BAR_W24 = 29, BAR_QST = 30, BAR_WOF = 31, BAR_WOE = 33,
              BAR_ATI = 35, BAR_ATD = 37, BAR_O = 39, BAR_OFREE = 40;
constexpr int SPIN_LIMIT = 1 << 22;

__device__ uint4 g_qkv[216 * SEQ];
__device__ uint32_t g_o[128 * 128 * 36];
__device__ unsigned g_cnt[16 * 32];
__device__ unsigned g_done;
__device__ unsigned g_epoch;

__device__ __forceinline__ uint32_t smem_u32(const void* p) { return (uint32_t)__cvta_generic_to_shared(p); }
__device__ __forceinline__ void wg_fence() { asm volatile("wgmma.fence.sync.aligned;\n" ::: "memory"); }
__device__ __forceinline__ void wg_commit() { asm volatile("wgmma.commit_group.sync.aligned;\n" ::: "memory"); }
template <int N> __device__ __forceinline__ void wg_wait() { asm volatile("wgmma.wait_group.sync.aligned %0;\n" ::"n"(N) : "memory"); }
__device__ __forceinline__ void mbar_init(uint32_t a, int c) { asm volatile("mbarrier.init.shared::cta.b64 [%0], %1;" ::"r"(a), "r"(c) : "memory"); }
__device__ __forceinline__ void mbar_expect(uint32_t a, uint32_t b) { asm volatile("mbarrier.arrive.expect_tx.shared::cta.b64 _, [%0], %1;" ::"r"(a), "r"(b) : "memory"); }
__device__ __forceinline__ void mbar_arrive(uint32_t a) { asm volatile("mbarrier.arrive.shared::cta.b64 _, [%0];" ::"r"(a) : "memory"); }
__device__ __forceinline__ uint32_t mbar_try(uint32_t a, uint32_t par) {
  uint32_t ok;
  asm volatile("{\n.reg .pred p;\nmbarrier.try_wait.parity.shared::cta.b64 p, [%1], %2;\nselp.u32 %0,1,0,p;\n}\n" : "=r"(ok) : "r"(a), "r"(par) : "memory");
  return ok;
}
__device__ __forceinline__ void mbar_wait(uint32_t a, uint32_t par) {
  int it = 0;
  while (true) {
    if (mbar_try(a, par)) break;
    if (++it > SPIN_LIMIT) __trap();
  }
}
__device__ __forceinline__ void fence_mbar_init() { asm volatile("fence.mbarrier_init.release.cluster;" ::: "memory"); }
__device__ __forceinline__ void fence_async_smem() { asm volatile("fence.proxy.async.shared::cta;\n" ::: "memory"); }
__device__ __forceinline__ void fence_async_gmem() { asm volatile("fence.proxy.async.global;\n" ::: "memory"); }
__device__ __forceinline__ void tma2d(uint32_t dst, const CUtensorMap* m, int c0, int c1, uint32_t bar) {
  asm volatile("cp.async.bulk.tensor.2d.shared::cluster.global.mbarrier::complete_tx::bytes [%0], [%1, {%3, %4}], [%2];" ::"r"(dst), "l"(m), "r"(bar), "r"(c0), "r"(c1) : "memory");
}
__device__ __forceinline__ void bulk_g2s(uint32_t dst, const void* src, uint32_t bytes, uint32_t bar) {
  asm volatile("cp.async.bulk.shared::cluster.global.mbarrier::complete_tx::bytes [%0], [%1], %2, [%3];" ::"r"(dst), "l"(src), "r"(bytes), "r"(bar) : "memory");
}
__device__ __forceinline__ void tma2d_store(const CUtensorMap* m, uint32_t src, int c0, int c1) {
  asm volatile("cp.async.bulk.tensor.2d.global.shared::cta.tile.bulk_group [%0, {%2, %3}], [%1];" ::"l"(m), "r"(src), "r"(c0), "r"(c1) : "memory");
}
__device__ __forceinline__ bool elect() {
  uint32_t p;
  asm volatile("{\n.reg .pred p;\nelect.sync _|p, 0xffffffff;\nselp.u32 %0, 1, 0, p;\n}\n" : "=r"(p));
  return p;
}
__device__ __forceinline__ void tma2d_red(const CUtensorMap* m, uint32_t src, int c0, int c1) {
  asm volatile("cp.reduce.async.bulk.tensor.2d.global.shared::cta.add.tile.bulk_group [%0, {%2, %3}], [%1];" ::"l"(m), "r"(src), "r"(c0), "r"(c1) : "memory");
}
__device__ __forceinline__ void bulk_commit() { asm volatile("cp.async.bulk.commit_group;" ::: "memory"); }
__device__ __forceinline__ void bulk_wait_all() { asm volatile("cp.async.bulk.wait_group 0;" ::: "memory"); }
__device__ __forceinline__ void bulk_wait_read_all() { asm volatile("cp.async.bulk.wait_group.read 0;" ::: "memory"); }
__device__ __forceinline__ void ldsm4(uint32_t addr, uint32_t& r0, uint32_t& r1, uint32_t& r2, uint32_t& r3) {
  asm volatile("ldmatrix.sync.aligned.m8n8.x4.shared.b16 {%0,%1,%2,%3}, [%4];" : "=r"(r0), "=r"(r1), "=r"(r2), "=r"(r3) : "r"(addr) : "memory");
}
__device__ __forceinline__ void ldsm4_tied(uint32_t zero, uint32_t addr, uint32_t& r0, uint32_t& r1, uint32_t& r2, uint32_t& r3) {
  asm volatile("{\n.reg .pred p;\nsetp.eq.u32 p, %5, 0;\n@p ldmatrix.sync.aligned.m8n8.x4.shared.b16 {%0,%1,%2,%3}, [%4];\n}\n"
               : "+r"(r0), "+r"(r1), "+r"(r2), "+r"(r3) : "r"(addr), "r"(zero) : "memory");
}
__device__ __forceinline__ void stsm4(uint32_t addr, uint32_t r0, uint32_t r1, uint32_t r2, uint32_t r3) {
  asm volatile("stmatrix.sync.aligned.m8n8.x4.shared.b16 [%0], {%1,%2,%3,%4};" ::"r"(addr), "r"(r0), "r"(r1), "r"(r2), "r"(r3) : "memory");
}
template <int N> __device__ __forceinline__ void lds(uint32_t addr, uint32_t* v) {
  if (N == 4) asm volatile("ld.shared.v4.b32 {%0,%1,%2,%3}, [%4];" : "=r"(v[0]), "=r"(v[1]), "=r"(v[2]), "=r"(v[3]) : "r"(addr));
  else if (N == 2) asm volatile("ld.shared.v2.b32 {%0,%1}, [%2];" : "=r"(v[0]), "=r"(v[1]) : "r"(addr));
  else asm volatile("ld.shared.b32 %0, [%1];" : "=r"(v[0]) : "r"(addr));
}
__device__ __forceinline__ uint32_t pack2(float lo, float hi) { uint32_t r; asm("cvt.rn.bf16x2.f32 %0, %1, %2;" : "=r"(r) : "f"(hi), "f"(lo)); return r; }
__device__ __forceinline__ float bf_lo(uint32_t v) { return __uint_as_float(v << 16); }
__device__ __forceinline__ float bf_hi(uint32_t v) { return __uint_as_float(v & 0xffff0000u); }
__device__ __forceinline__ uint32_t bsub2(uint32_t a, uint32_t b) { uint32_t r; asm("sub.rn.bf16x2 %0, %1, %2;" : "=r"(r) : "r"(a), "r"(b)); return r; }
__device__ __forceinline__ uint32_t bmul2(uint32_t a, uint32_t b) { uint32_t r; asm("mul.rn.bf16x2 %0, %1, %2;" : "=r"(r) : "r"(a), "r"(b)); return r; }
__device__ __forceinline__ float tanh_hw(float x) { float y; asm("tanh.approx.f32 %0, %1;" : "=f"(y) : "f"(x)); return y; }
__device__ __forceinline__ float ex2(float x) { float y; asm("ex2.approx.ftz.f32 %0, %1;" : "=f"(y) : "f"(x)); return y; }
__device__ __forceinline__ unsigned ld_acquire(const unsigned* p) { unsigned v; asm volatile("ld.acquire.gpu.global.u32 %0, [%1];" : "=r"(v) : "l"(p) : "memory"); return v; }
__device__ __forceinline__ void red_release(unsigned* p, unsigned v) { asm volatile("red.release.gpu.global.add.u32 [%0], %1;" ::"l"(p), "r"(v) : "memory"); }
__device__ __forceinline__ void wait_counter(const unsigned* p, unsigned target) {
  int it = 0;
  while ((int)(ld_acquire(p) - target) < 0) { __nanosleep(128); if (++it > SPIN_LIMIT) __trap(); }
}
__device__ __forceinline__ void mma16816(float (&d)[4], uint32_t a0, uint32_t a1, uint32_t a2, uint32_t a3, uint32_t b0, uint32_t b1) {
  asm volatile("mma.sync.aligned.m16n8k16.row.col.f32.bf16.bf16.f32 {%0,%1,%2,%3}, {%4,%5,%6,%7}, {%8,%9}, {%0,%1,%2,%3};"
               : "+f"(d[0]), "+f"(d[1]), "+f"(d[2]), "+f"(d[3]) : "r"(a0), "r"(a1), "r"(a2), "r"(a3), "r"(b0), "r"(b1));
}
__device__ __forceinline__ void mma1688(float (&d)[4], uint32_t a0, uint32_t a1, uint32_t b0) {
  asm volatile("mma.sync.aligned.m16n8k8.row.col.f32.bf16.bf16.f32 {%0,%1,%2,%3}, {%4,%5}, {%6}, {%0,%1,%2,%3};"
               : "+f"(d[0]), "+f"(d[1]), "+f"(d[2]), "+f"(d[3]) : "r"(a0), "r"(a1), "r"(b0));
}

template <int NA> __device__ __forceinline__ void wgmma_rs_n64(float (&d)[NA], uint32_t a0, uint32_t a1, uint32_t a2, uint32_t a3, uint64_t db, int sd) {
  asm volatile("{\n.reg .pred p;\nsetp.ne.b32 p, %37, 0;\n"
    "wgmma.mma_async.sync.aligned.m64n64k16.f32.bf16.bf16 {%0, %1, %2, %3, %4, %5, %6, %7, %8, %9, %10, %11, %12, %13, %14, %15, %16, %17, %18, %19, %20, %21, %22, %23, %24, %25, %26, %27, %28, %29, %30, %31}, {%32, %33, %34, %35}, %36, p, 1, 1, 1;\n"
    "}\n"
    : "+f"(d[0]), "+f"(d[1]), "+f"(d[2]), "+f"(d[3]), "+f"(d[4]), "+f"(d[5]), "+f"(d[6]), "+f"(d[7]), "+f"(d[8]), "+f"(d[9]), "+f"(d[10]), "+f"(d[11]), "+f"(d[12]), "+f"(d[13]), "+f"(d[14]), "+f"(d[15]), "+f"(d[16]), "+f"(d[17]), "+f"(d[18]), "+f"(d[19]), "+f"(d[20]), "+f"(d[21]), "+f"(d[22]), "+f"(d[23]), "+f"(d[24]), "+f"(d[25]), "+f"(d[26]), "+f"(d[27]), "+f"(d[28]), "+f"(d[29]), "+f"(d[30]), "+f"(d[31])
    : "r"(a0), "r"(a1), "r"(a2), "r"(a3), "l"(db), "r"(sd));
}

template <int NA> __device__ __forceinline__ void wgmma_ss_n64(float (&d)[NA], uint64_t da, uint64_t db, int sd) {
  asm volatile("{\n.reg .pred p;\nsetp.ne.b32 p, %34, 0;\n"
    "wgmma.mma_async.sync.aligned.m64n64k16.f32.bf16.bf16 {%0, %1, %2, %3, %4, %5, %6, %7, %8, %9, %10, %11, %12, %13, %14, %15, %16, %17, %18, %19, %20, %21, %22, %23, %24, %25, %26, %27, %28, %29, %30, %31}, %32, %33, p, 1, 1, 0, 1;\n"
    "}\n"
    : "+f"(d[0]), "+f"(d[1]), "+f"(d[2]), "+f"(d[3]), "+f"(d[4]), "+f"(d[5]), "+f"(d[6]), "+f"(d[7]), "+f"(d[8]), "+f"(d[9]), "+f"(d[10]), "+f"(d[11]), "+f"(d[12]), "+f"(d[13]), "+f"(d[14]), "+f"(d[15]), "+f"(d[16]), "+f"(d[17]), "+f"(d[18]), "+f"(d[19]), "+f"(d[20]), "+f"(d[21]), "+f"(d[22]), "+f"(d[23]), "+f"(d[24]), "+f"(d[25]), "+f"(d[26]), "+f"(d[27]), "+f"(d[28]), "+f"(d[29]), "+f"(d[30]), "+f"(d[31])
    : "l"(da), "l"(db), "r"(sd));
}

template <int NA> __device__ __forceinline__ void wgmma_rs_n88(float (&d)[NA], uint32_t a0, uint32_t a1, uint32_t a2, uint32_t a3, uint64_t db, int sd) {
  asm volatile("{\n.reg .pred p;\nsetp.ne.b32 p, %49, 0;\n"
    "wgmma.mma_async.sync.aligned.m64n88k16.f32.bf16.bf16 {%0, %1, %2, %3, %4, %5, %6, %7, %8, %9, %10, %11, %12, %13, %14, %15, %16, %17, %18, %19, %20, %21, %22, %23, %24, %25, %26, %27, %28, %29, %30, %31, %32, %33, %34, %35, %36, %37, %38, %39, %40, %41, %42, %43}, {%44, %45, %46, %47}, %48, p, 1, 1, 1;\n"
    "}\n"
    : "+f"(d[0]), "+f"(d[1]), "+f"(d[2]), "+f"(d[3]), "+f"(d[4]), "+f"(d[5]), "+f"(d[6]), "+f"(d[7]), "+f"(d[8]), "+f"(d[9]), "+f"(d[10]), "+f"(d[11]), "+f"(d[12]), "+f"(d[13]), "+f"(d[14]), "+f"(d[15]), "+f"(d[16]), "+f"(d[17]), "+f"(d[18]), "+f"(d[19]), "+f"(d[20]), "+f"(d[21]), "+f"(d[22]), "+f"(d[23]), "+f"(d[24]), "+f"(d[25]), "+f"(d[26]), "+f"(d[27]), "+f"(d[28]), "+f"(d[29]), "+f"(d[30]), "+f"(d[31]), "+f"(d[32]), "+f"(d[33]), "+f"(d[34]), "+f"(d[35]), "+f"(d[36]), "+f"(d[37]), "+f"(d[38]), "+f"(d[39]), "+f"(d[40]), "+f"(d[41]), "+f"(d[42]), "+f"(d[43])
    : "r"(a0), "r"(a1), "r"(a2), "r"(a3), "l"(db), "r"(sd));
}

template <int NA> __device__ __forceinline__ void wgmma_ss_n88(float (&d)[NA], uint64_t da, uint64_t db, int sd) {
  asm volatile("{\n.reg .pred p;\nsetp.ne.b32 p, %46, 0;\n"
    "wgmma.mma_async.sync.aligned.m64n88k16.f32.bf16.bf16 {%0, %1, %2, %3, %4, %5, %6, %7, %8, %9, %10, %11, %12, %13, %14, %15, %16, %17, %18, %19, %20, %21, %22, %23, %24, %25, %26, %27, %28, %29, %30, %31, %32, %33, %34, %35, %36, %37, %38, %39, %40, %41, %42, %43}, %44, %45, p, 1, 1, 0, 1;\n"
    "}\n"
    : "+f"(d[0]), "+f"(d[1]), "+f"(d[2]), "+f"(d[3]), "+f"(d[4]), "+f"(d[5]), "+f"(d[6]), "+f"(d[7]), "+f"(d[8]), "+f"(d[9]), "+f"(d[10]), "+f"(d[11]), "+f"(d[12]), "+f"(d[13]), "+f"(d[14]), "+f"(d[15]), "+f"(d[16]), "+f"(d[17]), "+f"(d[18]), "+f"(d[19]), "+f"(d[20]), "+f"(d[21]), "+f"(d[22]), "+f"(d[23]), "+f"(d[24]), "+f"(d[25]), "+f"(d[26]), "+f"(d[27]), "+f"(d[28]), "+f"(d[29]), "+f"(d[30]), "+f"(d[31]), "+f"(d[32]), "+f"(d[33]), "+f"(d[34]), "+f"(d[35]), "+f"(d[36]), "+f"(d[37]), "+f"(d[38]), "+f"(d[39]), "+f"(d[40]), "+f"(d[41]), "+f"(d[42]), "+f"(d[43])
    : "l"(da), "l"(db), "r"(sd));
}


__device__ __forceinline__ uint64_t mkd(uint32_t lo) { return ((uint64_t)0x40000040u << 32) | (uint64_t)lo; }

constexpr uint32_t sr = 1024, sb = sr + RING;
constexpr uint32_t bars = sb + OFF_BAR;
constexpr uint32_t RING_LO = (sr >> 4) | (512u << 16);

template <int NA> __device__ __forceinline__ void acc_fence(float (&d)[NA]) {
  asm volatile("" : "+f"(d[0]), "+f"(d[1]), "+f"(d[2]), "+f"(d[3]), "+f"(d[4]), "+f"(d[5]), "+f"(d[6]), "+f"(d[7]), "+f"(d[8]), "+f"(d[9]), "+f"(d[10]), "+f"(d[11]), "+f"(d[12]), "+f"(d[13]), "+f"(d[14]), "+f"(d[15]), "+f"(d[16]), "+f"(d[17]), "+f"(d[18]), "+f"(d[19]), "+f"(d[20]), "+f"(d[21]), "+f"(d[22]), "+f"(d[23]), "+f"(d[24]), "+f"(d[25]), "+f"(d[26]), "+f"(d[27]), "+f"(d[28]), "+f"(d[29]), "+f"(d[30]), "+f"(d[31]) :: "memory");
}

template <int V> struct IC { static constexpr int value = V; };

template <int PH, bool FIRST, int NA, class M, class F>
__device__ __forceinline__ void run_pass(float (&other)[NA], M&& mma, F&& slice) {
#pragma unroll
  for (int s = 0; s < 9; s++) {
    wg_fence();
    mma(s, RING_LO + s * (SLOT >> 4));
    wg_commit();
    mbar_wait(bars + (BAR_FULL + (s + 1) % 9) * 8, s < 8 ? PH : PH ^ 1);
    slice(s);
    wg_wait<1>();
    if (s == 0) acc_fence(other);
    if ((s || !FIRST) && (threadIdx.x & 127) == 0) mbar_arrive(bars + (BAR_EMPTY + (s + 8) % 9) * 8);
  }
}

template <int BUF, int PH, bool FIRST, int NA, class M, class F>
__device__ __forceinline__ void run_down(uint32_t wpar, bool last, float (&other)[NA], M&& mma, F&& slice) {
#pragma unroll
  for (int s = 0; s < 10; s++) {
    wg_fence();
    mma(s, s < 9 ? RING_LO + s * (SLOT >> 4) : ((sb + 8 * HS + BUF * SLOT) >> 4) | (512u << 16));
    wg_commit();
    if (s < 8) mbar_wait(bars + (BAR_FULL + s + 1) * 8, PH);
    else if (s == 8) mbar_wait(bars + (BAR_WOF + BUF) * 8, wpar);
    else if (!last) mbar_wait(bars + BAR_FULL * 8, PH ^ 1);
    slice(s);
    wg_wait<1>();
    if (s == 0) acc_fence(other);
    if ((threadIdx.x & 127) == 0) {
      if (s) mbar_arrive(bars + (BAR_EMPTY + s - 1) * 8);
      else {
        if (FIRST) { mbar_arrive(bars + (BAR_EMPTY + 8) * 8); mbar_arrive(bars + (BAR_WOE + BUF) * 8); }
        mbar_arrive(bars + (BAR_WOE + (BUF ^ 1)) * 8);
      }
    }
  }
}

struct Maps {
  CUtensorMap x, wqkv, w24, wg, wu, wd, woa, wob, out, lkv, lq, op;
};

__global__ void __launch_bounds__(384, 1)
fused_kernel(const __grid_constant__ Maps mp, const void* __restrict__ wqkv, uint32_t zero) {
  extern __shared__ __align__(1024) uint8_t smem[];
  const int j = (blockIdx.x >> 2) & 7, m = (blockIdx.x & 3) + ((blockIdx.x >> 3) & 12);
  const int m0 = m * 128;
  if (threadIdx.x == 256) {
#pragma unroll
    for (int i = 0; i < 9; i++) {
      const uint32_t b = bars + (BAR_X + i) * 8;
      mbar_init(b, 1);
      fence_mbar_init();
      mbar_expect(b, HS);
      tma2d(sb + i * HS, &mp.x, i * 64, m0, b);
    }
  }
  const int warp = __shfl_sync(0xffffffffu, threadIdx.x >> 5, 0), lane = threadIdx.x & 31;

  asm volatile("" ::: "memory");
  if (lane == 0) {
    if (warp == 9) {
      if (smem_u32(smem) != sr) __trap();
      for (int i = 0; i < NSLOT; i++) { mbar_init(bars + (BAR_FULL + i) * 8, 1); mbar_init(bars + (BAR_EMPTY + i) * 8, 2); }
      fence_mbar_init();
    } else if (warp == 10) {
      mbar_init(bars + BAR_WOR * 8, 1);
      mbar_init(bars + BAR_XDONE * 8, 9);
      mbar_init(bars + BAR_W24 * 8, 1);
      mbar_init(bars + BAR_QST * 8, 8);
      for (int i = 0; i < 2; i++) { mbar_init(bars + (BAR_WOF + i) * 8, 1); mbar_init(bars + (BAR_WOE + i) * 8, 2); }
      for (int i = 0; i < 2; i++) { mbar_init(bars + (BAR_ATI + i) * 8, 1); mbar_init(bars + (BAR_ATD + i) * 8, 1); }
      mbar_init(bars + BAR_O * 8, 1);
      mbar_init(bars + BAR_OFREE * 8, 8);
      fence_mbar_init();
    }
  }
  __syncthreads();

  if (warp < 8) {
    asm volatile("setmaxnreg.inc.sync.aligned.u32 232;\n");
    const int wg = warp >> 2;
    const int lrow = (warp & 3) * 16 + (lane & 15);
    const uint32_t rowa = sb + wg * 8192 + lrow * 128;
    const uint32_t swz = ((lane >> 4) ^ (lrow & 7)) << 4;
    uint32_t adr[4];
#pragma unroll
    for (int i = 0; i < 4; i++) { adr[i] = rowa + (swz ^ (i << 5)); asm volatile("" : "+r"(adr[i])); }
    uint32_t a[128];
    uint32_t sg[16], oq[4], oz[4];
    float accA[32], accB[44];
    float rs0, rs1, rh0, rh1;
    uint32_t mp0, mp1;
    {
      float cs[2][4] = {}, c1[2][4] = {}, c2[2][4] = {};
      mbar_wait(bars + BAR_X * 8, 0);
#pragma unroll
      for (int kb = 0; kb < 9; kb++) {
        uint32_t ok = 1;
        if (kb < 8) ok = mbar_try(bars + (BAR_X + kb + 1) * 8, 0);
        uint32_t* r = (kb < 8) ? &a[kb * 16] : sg;
#pragma unroll
        for (int kk = 0; kk < 4; kk++) ldsm4(adr[kk] + kb * HS, r[kk * 4], r[kk * 4 + 1], r[kk * 4 + 2], r[kk * 4 + 3]);
#pragma unroll
        for (int kk = 0; kk < 4; kk++, r += 4) {
          mma16816(cs[kk & 1], r[0], r[1], r[2], r[3], 0x3f803f80u, 0x3f803f80u);
          mma1688(c1[0], r[0], r[1], r[0]);
          mma1688(c2[0], r[0], r[1], r[1]);
          mma1688(c1[1], r[2], r[3], r[2]);
          mma1688(c2[1], r[2], r[3], r[3]);
        }
        if (!ok) mbar_wait(bars + (BAR_X + kb + 1) * 8, 0);
      }
      __syncwarp();
      if (lane == 0) mbar_arrive(bars + BAR_XDONE * 8);
      const float mu0 = (cs[0][0] + cs[1][0]) * (1.f / DM), mu1 = (cs[0][2] + cs[1][2]) * (1.f / DM);
      mp0 = pack2(mu0, mu0); mp1 = pack2(mu1, mu1);
      rs0 = (lane & 4) ? c1[0][1] + c1[1][1] : c1[0][0] + c1[1][0];
      rs1 = (lane & 4) ? c2[0][3] + c2[1][3] : c2[0][2] + c2[1][2];
      rh0 = mu0 * mu0; rh1 = mu1 * mu1;
    }
    auto finish_rstd = [&]() {
      const int src = (lane & ~3) | (lane >> 3);
      rs0 = rsqrtf(fmaxf(__shfl_sync(0xffffffffu, rs0, src) * (1.f / DM) - rh0, 0.f) + 1e-5f);
      rs1 = rsqrtf(fmaxf(__shfl_sync(0xffffffffu, rs1, src) * (1.f / DM) - rh1, 0.f) + 1e-5f);
      rh0 = 0.5f * rs0; rh1 = 0.5f * rs1;
    };
    auto centre = [&](int kb) {
#pragma unroll
      for (int i = kb * 16; i < kb * 16 + 16; i++) a[i] = bsub2(a[i], (i & 1) ? mp1 : mp0);
    };
    centre(0);

    const uint32_t xlo = ((sb + 8 * HS + wg * 8192) >> 4) | (1u << 16);

    auto rs64 = [&](auto& acc, int kb, uint32_t blo, bool first) {
#pragma unroll
      for (int kk = 0; kk < 4; kk++)
        wgmma_rs_n64(acc, a[kb * 16 + kk * 4], a[kb * 16 + kk * 4 + 1], a[kb * 16 + kk * 4 + 2], a[kb * 16 + kk * 4 + 3], mkd(blo + kk * 128), !(first && kk == 0));
    };
    auto ss64 = [&](auto& acc, int slot, uint32_t blo) {
#pragma unroll
      for (int kk = 0; kk < 4; kk++) wgmma_ss_n64(acc, mkd(xlo - (8 - slot) * (HS >> 4) + kk * 2), mkd(blo + kk * 128), 1);
    };
    auto mma64 = [&](auto& acc, int s, uint32_t blo) { if (s < 8) rs64(acc, s, blo, s == 0); else ss64(acc, 8, blo); };
    char* qp = reinterpret_cast<char*>(g_qkv + (j * 24) * SEQ + m0 + (threadIdx.x >> 5) * 16) + (threadIdx.x & 31) * 4;
    auto qkv_store = [&](const auto& acc, int nb, int chunk) {
      *reinterpret_cast<uint32_t*>(qp + chunk * (SEQ * 16)) = pack2(acc[4 * nb] * rs0, acc[4 * nb + 1] * rs0);
      *reinterpret_cast<uint32_t*>(qp + chunk * (SEQ * 16) + 128) = pack2(acc[4 * nb + 2] * rs1, acc[4 * nb + 3] * rs1);
    };
    auto sig_slice = [&](const auto& acc, int s) {
      if (s >= 1) {
#pragma unroll
        for (int e = 2 * (s - 1); e < 2 * s; e++) {
          const float r = (e & 1) ? rh1 : rh0;
          sg[e] = pack2(fmaf(tanh_hw(acc[2 * e] * r), r, r), fmaf(tanh_hw(acc[2 * e + 1] * r), r, r));
        }
      }
    };
    auto h_val = [&](const auto& acc, int e) { return bmul2(sg[e], pack2(acc[2 * e], acc[2 * e + 1])); };
    auto load_h = [&](int pos) {
#pragma unroll
      for (int kk = (pos & 1) * 2; kk < (pos & 1) * 2 + 2; kk++) {
        const int kb = pos >> 1;
        ldsm4_tied(zero, adr[kk] + kb * HS, a[kb * 16 + kk * 4], a[kb * 16 + kk * 4 + 1], a[kb * 16 + kk * 4 + 2], a[kb * 16 + kk * 4 + 3]);
      }
    };

    mbar_wait(bars + BAR_FULL * 8, 0);
    run_pass<0, true>(accA, [&](int s, uint32_t b) { mma64(accB, s, b); }, [&](int s) {
      if (s < 7) centre(s + 1);
      if (s == 0) finish_rstd();
      if (s == 6) {
        mbar_wait(bars + BAR_XDONE * 8, 0);
#pragma unroll
        for (int i = 0; i < 16; i++) sg[i] = bsub2(sg[i], (i & 1) ? mp1 : mp0);
#pragma unroll
        for (int kk = 0; kk < 4; kk++) stsm4(adr[kk] + 8 * HS, sg[kk * 4], sg[kk * 4 + 1], sg[kk * 4 + 2], sg[kk * 4 + 3]);
        fence_async_smem();
      }
      if (s == 7) asm volatile("bar.sync %0, 128;" ::"r"(1 + wg) : "memory");
    });
    run_pass<1, false>(accB, [&](int s, uint32_t b) { mma64(accA, s, b); }, [&](int s) {
      if (s >= 1) qkv_store(accB, s - 1, s - 1);
      if (s == 8) mbar_wait(bars + BAR_W24 * 8, 0);
    });
    run_pass<0, false>(accA, [&](int s, uint32_t b) {
      const uint32_t lo = (b & 0xffffu) | (((OFF_W24 + RING) >> 4) << 16);
#pragma unroll
      for (int kk = 0; kk < 4; kk++) {
        const int k = s * 4 + kk;
        if (s < 8) wgmma_rs_n88(accB, a[k * 4], a[k * 4 + 1], a[k * 4 + 2], a[k * 4 + 3], mkd(lo + kk * 128), k != 0);
        else wgmma_ss_n88(accB, mkd(xlo + kk * 2), mkd(lo + kk * 128), 1);
      }
    }, [&](int s) { if (s >= 1) qkv_store(accA, s - 1, 7 + s); });
    run_pass<1, false>(accB, [&](int s, uint32_t b) { mma64(accA, s, b); }, [&](int s) {
      if (s == 1) asm volatile("" : "+f"(accB[32]), "+f"(accB[33]), "+f"(accB[34]), "+f"(accB[35]), "+f"(accB[36]), "+f"(accB[37]), "+f"(accB[38]),
                               "+f"(accB[39]), "+f"(accB[40]), "+f"(accB[41]), "+f"(accB[42]), "+f"(accB[43]) :: "memory");
      if (s >= 1 && s <= 4) { qkv_store(accB, 2 * s - 2, 14 + 2 * s); qkv_store(accB, 2 * s - 1, 15 + 2 * s); }
      if (s == 5) { qp += (192 - 21 * j) * (SEQ * 16); qkv_store(accB, 8, 0); qkv_store(accB, 9, 1); }
      if (s == 6) {
        qkv_store(accB, 10, 2);
        __syncwarp();
        if (lane == 0) mbar_arrive(bars + BAR_QST * 8);
      }
    });
    for (int c = 0; c < 8; c++) {
      run_pass<0, false>(accA, [&](int s, uint32_t b) { mma64(accB, s, b); }, [&](int s) { sig_slice(accA, s); });
      run_pass<1, false>(accB, [&](int s, uint32_t b) { mma64(accA, s, b); }, [&](int s) {
        if (s == 1 && c >= 6) mbar_wait(bars + (BAR_ATD - 6 + c) * 8, 0);
        if (s >= 1 && s <= 7 && (s & 1)) {
          const int t = s >> 1;
          stsm4(adr[t] + c * HS, h_val(accB, 4 * t), h_val(accB, 4 * t + 1), h_val(accB, 4 * t + 2), h_val(accB, 4 * t + 3));
        }
      });
    }
    run_pass<0, false>(accA, [&](int s, uint32_t b) { mma64(accB, s, b); }, [&](int s) {
      sig_slice(accA, s);
      if (s == 0) {
        fence_async_smem();
        asm volatile("bar.sync %0, 128;" ::"r"(1 + wg) : "memory");
      }
      if (s >= 2) load_h(s - 2);
      if (s == 6) {
        __syncwarp();
        if (lane == 0) mbar_arrive(bars + BAR_OFREE * 8);
      }
    });
    constexpr uint32_t worlo = ((sb + OFF_WOR) >> 4) | (512u << 16);
    const int grow = m0 + warp * 16;
    int blk = j;
    auto mmaD = [&](auto& acc, int s, uint32_t blo, const uint32_t* sh, uint32_t shlo) {
      if (s < 6) rs64(acc, s, blo, s == 0);
      else if (s < 8) ss64(acc, s, blo);
      else rs64(acc, s - 2, blo, false);
      if (s == 9 && sh) wgmma_rs_n64(acc, sh[0], sh[1], sh[2], sh[3], mkd(shlo), 1);
    };
    auto flush_store = [&](const auto& acc, int slot, int t) {
      stsm4(adr[t] + slot * HS, pack2(acc[8 * t], acc[8 * t + 1]), pack2(acc[8 * t + 2], acc[8 * t + 3]),
            pack2(acc[8 * t + 4], acc[8 * t + 5]), pack2(acc[8 * t + 6], acc[8 * t + 7]));
    };
    auto flush_issue = [&](int slot, int cb) {
      fence_async_smem();
      __syncwarp();
      if (elect()) { tma2d_red(&mp.out, sb + slot * HS + warp * 2048, cb * 64, grow); bulk_commit(); }
    };
    run_down<0, 1, true>(0, false, accB, [&](int s, uint32_t b) { mmaD(accA, s, b, oz, ((sb + OFF_WO0) >> 4) | (512u << 16)); }, [&](int s) {
      if (s < 5) load_h(7 + s);
      if (s >= 1 && s <= 4) {
#pragma unroll
        for (int e = 4 * (s - 1); e < 4 * s; e++) a[96 + e] = h_val(accB, e);
      }
      if (s == 7) {
        mbar_wait(bars + BAR_WOR * 8, 0);
        mbar_wait(bars + BAR_O * 8, 0);
        fence_async_gmem();
        const uint32_t orow = (threadIdx.x >> 5) * 16 + (threadIdx.x & 15), oa = sb + orow * 144, odd = j & 1;
#pragma unroll
        for (int kk = 0; kk < 4; kk++) ldsm4(oa + odd * 16 + kk * 32 + (threadIdx.x & 16), a[112 + kk * 4], a[113 + kk * 4], a[114 + kk * 4], a[115 + kk * 4]);
        ldsm4(((threadIdx.x >> 4) & 1) == odd ? oa + 128 - odd * 128 : sb + OFF_OP + orow * 16, oq[0], oq[1], oq[2], oq[3]);
#pragma unroll
        for (int i = 0; i < 4; i++) asm volatile("mul.lo.u32 %0, %1, %2;" : "=r"(oz[i]) : "r"(oq[i]), "r"(odd ^ 1));
      }
    });
    auto flush_slice = [&](const auto& acc, int slot, int cb, int s) {
      if (s == 0) { asm volatile("cp.async.bulk.wait_group.read 1;" ::: "memory"); __syncwarp(); }
      if (s >= 1 && s <= 4) flush_store(acc, slot, s - 1);
      if (s == 5) flush_issue(slot, cb);
    };
    for (int p = 1; p < 9; p += 2) {
      int pb = blk; blk = (blk == 8) ? 0 : blk + 1;
      run_down<1, 0, false>((p >> 1) & 1, false, accA, [&](int s, uint32_t b) { mmaD(accB, s, b, oq, worlo + (p >> 1) * 128); }, [&](int s) { flush_slice(accA, 2, pb, s); });
      pb = blk; blk = (blk == 8) ? 0 : blk + 1;
      if (p == 7 && wg == 1) asm volatile("bar.sync 5, 256;" ::: "memory");
      run_down<0, 1, false>(((p + 1) >> 1) & 1, p == 7, accB, [&](int s, uint32_t b) { mmaD(accA, s, b, nullptr, 0); }, [&](int s) {
        flush_slice(accB, 3, pb, s);
        if (s == 3 && p == 7 && wg == 0) asm volatile("bar.arrive 5, 256;" ::: "memory");
      });
    }
    flush_slice(accA, 2, blk, 0);
    wg_wait<0>();
    acc_fence(accA);
#pragma unroll
    for (int t = 1; t <= 5; t++) flush_slice(accA, 2, blk, t);
    bulk_wait_read_all();
  } else {
    asm volatile("setmaxnreg.dec.sync.aligned.u32 40;\n");
    if (warp == 8) {
      int st = 0; uint32_t ph = 1;
      auto stage = [&](const CUtensorMap* w, int c0, int c1) {
        mbar_wait(bars + (BAR_EMPTY + st) * 8, ph);
        const uint32_t fb = bars + (BAR_FULL + st) * 8;
        if (elect()) {
          mbar_expect(fb, SLOT);
          tma2d(sr + st * SLOT, w, c0, c1, fb);
        }
        st++;
        if (st == NSLOT) { st = 0; ph ^= 1; }
      };
      int blk = j;
#pragma unroll 1
      for (int p = 0; p < 30; p++) {
        const CUtensorMap* w; int c0, c1 = 0;
        if (p < 3) { w = &mp.wqkv; c0 = j * 192 + p * 64; }
        else if (p < 21) { w = (p & 1) ? &mp.wg : &mp.wu; c0 = j * 576 + ((p - 3) >> 1) * 64; }
        else { w = &mp.wd; c0 = blk * 64; c1 = j * 576; }
#pragma unroll 1
        for (int kb = 0; kb < 9; kb++) {
          stage(w, c0, c1 + kb * 64);
        }
        if (p >= 21) {
          const int q = p - 21;
          mbar_wait(bars + (BAR_WOE + (q & 1)) * 8, (q >> 1) & 1);
          if (elect()) {
            mbar_expect(bars + (BAR_WOF + (q & 1)) * 8, SLOT);
            tma2d(sb + 8 * HS + (q & 1) * SLOT, &mp.woa, c0, j * 72 + (j & 1) * 8, bars + (BAR_WOF + (q & 1)) * 8);
          }
          blk = (blk == 8) ? 0 : blk + 1;
        }
      }
    } else {
      const int aw = warp - 9;
      if (aw == 2 && elect()) {
        const CUtensorMap* mm = &mp.w24;
#pragma unroll 1
        for (int i = 0; i < 10; i++) asm volatile("prefetch.tensormap [%0];" ::"l"(mm + i) : "memory");
      }
      const unsigned target = (*(volatile unsigned*)&g_epoch + 1) * 8;
      if (aw == 1) {
#pragma unroll 1
        for (int kb = 0; kb < 9; kb++) {
          mbar_wait(bars + (BAR_X + kb) * 8, 0);
          if (elect()) tma2d_store(&mp.out, sb + kb * HS + j * 2048, kb * 64, m0 + j * 16);
        }
        if (elect()) bulk_commit();
        bulk_wait_read_all();
        __syncwarp();
        if (lane == 0) mbar_arrive(bars + BAR_XDONE * 8);
      }
      mbar_wait(bars + (BAR_X + 4) * 8, 0);
      for (int u = aw * 32 + lane; u < 36 * 4; u += 96) {
        const int r = m * 36 + (u >> 2), c = u & 3;
        asm volatile("prefetch.global.L2 [%0];" ::"l"(reinterpret_cast<const char*>(wqkv) + (size_t)r * (3 * DM * 2) + (c < 3 ? j * 384 + c * 128 : 3072 + j * 48)));
      }
      if (aw == 2) {
        mbar_wait(bars + BAR_XDONE * 8, 0);
        if (elect()) { mbar_expect(bars + BAR_W24 * 8, 9 * 64 * 48); mbar_expect(bars + BAR_WOR * 8, 4 * 2048); }
#pragma unroll 1
        for (int b = 0; b < 13; b++) {
          if (elect()) {
            if (b < 9) tma2d(sb + OFF_W24 + b * SLOT, &mp.w24, 1536 + j * 24, b * 64, bars + BAR_W24 * 8);
            else tma2d(sb + OFF_WOR + (b - 9) * 2048, &mp.wob, ((j + 2 * b - 17) % 9) * 64, (j & ~1) * 72 + 64, bars + BAR_WOR * 8);
          }
          __nanosleep(64);
        }
      }
      if (aw == 1) bulk_wait_all();
      asm volatile("bar.sync 3, 96;" ::: "memory");
      auto load_kq = [&](int t) {
        const int r2 = (m0 + t * 48) * 2;
        mbar_expect(bars + BAR_ATI * 8, 9 * (62 + 50) * 16);
        tma2d(sb + OFF_AK, &mp.lkv, r2 - 28, 72 + j * 9, bars + BAR_ATI * 8);
        tma2d(sb + OFF_AQ, &mp.lq, r2, j * 9, bars + BAR_ATI * 8);
      };
      auto load_v = [&](int t) {
        mbar_expect(bars + (BAR_ATI + 1) * 8, 9 * 62 * 16);
        tma2d(sb + OFF_AV, &mp.lkv, (m0 + t * 48) * 2 - 28, 144 + j * 9, bars + (BAR_ATI + 1) * 8);
      };
      if (aw == 0) {
        mbar_wait(bars + BAR_QST * 8, 0);
        if (lane == 0) {
          red_release(&g_cnt[m * 32], 1);
        }
        if (lane < 2) wait_counter(&g_cnt[(lane && m ? m - 1 : m) * 32], target);
        __syncwarp();
        fence_async_gmem();
        if (elect()) { load_kq(0); load_v(0); }
      }
      uint32_t l16 = (aw * 16 + (lane & 1) + (lane & 2) * 2 + (lane >> 4) * 8) * 16;
      auto fresh = [&]() { asm volatile("" : "+r"(l16)); return l16; };
      const float sc = 0.23570226039551584f * 1.4426950408889634f;
#pragma unroll 1
      for (int t = 0; t < 3; t++) {
        const bool active = t < 2 || aw < 2;
        float p0[8] = {}, p1[8] = {};
        uint32_t h8 = (threadIdx.x & 12) * 2;
        asm volatile("" : "+r"(h8));
        const uint32_t po = (0x70482800u >> h8) & 255, po3 = (0x6C682420u >> h8) & 255;
        const uint32_t px = (0x00100000u >> h8) & 255;
        mbar_wait(bars + BAR_ATI * 8, t & 1);
        if (active) {
          auto qk = [&](auto nw, uint32_t b) {
            constexpr int N = decltype(nw)::value;
            uint32_t u[N]; float q0[2 * N], q1[2 * N];
            const uint32_t o = fresh() + (b & 15), qa = o + (b >> 4) * 800 + (sb + OFF_AQ), ka = o + (b >> 4) * 992 + (sb + OFF_AK);
            lds<N>(qa, u);
#pragma unroll
            for (int i = 0; i < N; i++) { q0[2 * i] = bf_lo(u[i]); q0[2 * i + 1] = bf_hi(u[i]); }
            lds<N>(qa + 32, u);
#pragma unroll
            for (int i = 0; i < N; i++) { q1[2 * i] = bf_lo(u[i]); q1[2 * i + 1] = bf_hi(u[i]); }
#pragma unroll
            for (int s = 0; s < 9; s++) {
              lds<N>(ka + (16 - 2 * s) * 16, u);
#pragma unroll
              for (int i = 0; i < N; i++) {
                const float lo = bf_lo(u[i]), hi = bf_hi(u[i]);
                if (s < 8) { p1[s] = fmaf(q1[2 * i], lo, p1[s]); p1[s] = fmaf(q1[2 * i + 1], hi, p1[s]); }
                if (s > 0) { p0[s - 1] = fmaf(q0[2 * i], lo, p0[s - 1]); p0[s - 1] = fmaf(q0[2 * i + 1], hi, p0[s - 1]); }
              }
            }
          };
#pragma unroll 1
          for (int i = 0; i < 4; i++) qk(IC<2>(), po + ((8 * i) ^ px));
          qk(IC<1>(), po3);
        }
        asm volatile("bar.sync 3, 96;" ::: "memory");
        if (aw == 0 && elect()) { if (t < 2) load_kq(t + 1); else mbar_arrive(bars + BAR_ATD * 8); }
        if (active) {
          if (m0 + t == 0) {
            const int row = fresh() >> 4;
#pragma unroll
            for (int w = 1; w < 8; w++) { if (row < 2 * w) p0[w] = -INFINITY; if (row + 2 < 2 * w) p1[w] = -INFINITY; }
          }
          auto softmax = [&](float (&p)[8]) {
            const float mx = fmaxf(fmaxf(fmaxf(p[0], p[1]), fmaxf(p[2], p[3])), fmaxf(fmaxf(p[4], p[5]), fmaxf(p[6], p[7])));
            const float ms = -mx * sc;
            float l = 0.f;
#pragma unroll
            for (int w = 0; w < 8; w++) { p[w] = ex2(fmaf(p[w], sc, ms)); l += p[w]; }
            l = __fdividef(1.f, l);
#pragma unroll
            for (int w = 0; w < 8; w++) p[w] *= l;
          };
          softmax(p0); softmax(p1);
        }
        mbar_wait(bars + (BAR_ATI + 1) * 8, t & 1);
        if (active) {
          char* op = reinterpret_cast<char*>(g_o + (blockIdx.x * 128 + t * 48) * 36) + fresh() * 9;
          auto pv = [&](auto nw, uint32_t b) {
            constexpr int N = decltype(nw)::value;
            uint32_t u[N]; float o0[2 * N] = {}, o1[2 * N] = {};
            const uint32_t va = fresh() + (b & 15) + (b >> 4) * 992 + (sb + OFF_AV);
#pragma unroll
            for (int s = 0; s < 9; s++) {
              lds<N>(va + (16 - 2 * s) * 16, u);
#pragma unroll
              for (int i = 0; i < N; i++) {
                const float lo = bf_lo(u[i]), hi = bf_hi(u[i]);
                if (s < 8) { o1[2 * i] = fmaf(p1[s], lo, o1[2 * i]); o1[2 * i + 1] = fmaf(p1[s], hi, o1[2 * i + 1]); }
                if (s > 0) { o0[2 * i] = fmaf(p0[s - 1], lo, o0[2 * i]); o0[2 * i + 1] = fmaf(p0[s - 1], hi, o0[2 * i + 1]); }
              }
            }
            if (N == 2) {
              *reinterpret_cast<uint2*>(op + b) = make_uint2(pack2(o0[0], o0[1]), pack2(o0[2 % (2 * N)], o0[3 % (2 * N)]));
              *reinterpret_cast<uint2*>(op + b + 288) = make_uint2(pack2(o1[0], o1[1]), pack2(o1[2 % (2 * N)], o1[3 % (2 * N)]));
            } else {
              *reinterpret_cast<uint32_t*>(op + b) = pack2(o0[0], o0[1]);
              *reinterpret_cast<uint32_t*>(op + b + 288) = pack2(o1[0], o1[1]);
            }
          };
#pragma unroll 1
          for (int i = 0; i < 4; i++) pv(IC<2>(), po + ((8 * i) ^ px));
          pv(IC<1>(), po3);
        }
        asm volatile("bar.sync 3, 96;" ::: "memory");
        if (aw == 0 && elect()) { if (t < 2) load_v(t + 1); else mbar_arrive(bars + (BAR_ATD + 1) * 8); }
      }
      if (aw == 0) {
        if (elect()) {
          red_release(&g_cnt[m * 32 + 8 + (j >> 1)], 1);
          wait_counter(&g_cnt[m * 32 + 8 + (j >> 1)], (*(volatile unsigned*)&g_epoch + 1) * 2);
        }
        __syncwarp();
        mbar_wait(bars + BAR_OFREE * 8, 0);
        fence_async_gmem();
        if (elect()) {
          mbar_expect(bars + BAR_O * 8, OTILE + 4096);
          bulk_g2s(sb, g_o + blockIdx.x * 128 * 36, OTILE, bars + BAR_O * 8);
          tma2d(sb + OFF_OP, &mp.op, (j & 1) * 16, (blockIdx.x ^ 4) * 128, bars + BAR_O * 8);
          tma2d(sb + OFF_WO0, &mp.wob, j * 64, (j & ~1) * 72 + 64, bars + BAR_O * 8);
          if (atomicInc(&g_done, 127u) == 127u) atomicAdd(&g_epoch, 1u);
        }
      }
    }
  }
}

typedef CUresult (*EncodeFn)(CUtensorMap*, CUtensorMapDataType, cuuint32_t, void*, const cuuint64_t*, const cuuint64_t*, const cuuint32_t*,
                             const cuuint32_t*, CUtensorMapInterleave, CUtensorMapSwizzle, CUtensorMapL2promotion, CUtensorMapFloatOOBfill);

void encode2(EncodeFn fn, CUtensorMap* m, const void* p, uint64_t cols, uint64_t rows, uint32_t bc, uint32_t br, bool raw = false,
             CUtensorMapL2promotion promo = CU_TENSOR_MAP_L2_PROMOTION_L2_128B) {
  const cuuint64_t d[2] = {cols, rows}, s[1] = {cols * (raw ? 8 : 2)};
  const cuuint32_t b[2] = {bc, br}, es[2] = {1, 1};
  fn(m, raw ? CU_TENSOR_MAP_DATA_TYPE_UINT64 : CU_TENSOR_MAP_DATA_TYPE_BFLOAT16, 2, const_cast<void*>(p), d, s, b, es, CU_TENSOR_MAP_INTERLEAVE_NONE,
     raw ? CU_TENSOR_MAP_SWIZZLE_NONE : CU_TENSOR_MAP_SWIZZLE_128B, promo, CU_TENSOR_MAP_FLOAT_OOB_FILL_NONE);
}

}

extern "C" void kernel_launch(void* const* d_in, const int* in_sizes, int n_in, void* d_out, int out_size) {
  void* fp = nullptr;
  cudaDriverEntryPointQueryResult qr;
  cudaGetDriverEntryPoint("cuTensorMapEncodeTiled", &fp, cudaEnableDefault, &qr);
  EncodeFn fn = (EncodeFn)fp;
  void* qkv = nullptr;
  cudaGetSymbolAddress(&qkv, g_qkv);
  Maps mp;
  encode2(fn, &mp.x, d_in[0], DM, SEQ, 64, 128, false, CU_TENSOR_MAP_L2_PROMOTION_L2_256B);
  encode2(fn, &mp.wqkv, d_in[1], 3 * DM, DM, 64, 64);
  encode2(fn, &mp.w24, d_in[1], 3 * DM, DM, 24, 64);
  encode2(fn, &mp.wg, d_in[4], FF, DM, 64, 64);
  encode2(fn, &mp.wu, d_in[5], FF, DM, 64, 64);
  encode2(fn, &mp.wd, d_in[6], DM, FF, 64, 64);
  encode2(fn, &mp.woa, d_in[2], DM, DM, 64, 64);
  encode2(fn, &mp.wob, d_in[2], DM, DM, 64, 16);
  encode2(fn, &mp.out, d_out, DM, SEQ, 64, 16);
  encode2(fn, &mp.lkv, qkv, 2 * SEQ, 216, 124, 9, true);
  void* op = nullptr;
  cudaGetSymbolAddress(&op, g_o);
  encode2(fn, &mp.op, op, 18, 128 * 128, 2, 128, true);
  encode2(fn, &mp.lq, qkv, 2 * SEQ, 216, 100, 9, true);
  cudaFuncSetAttribute(fused_kernel, cudaFuncAttributeMaxDynamicSharedMemorySize, SMEM_BYTES);
  fused_kernel<<<128, 384, SMEM_BYTES, cudaStreamPerThread>>>(mp, d_in[1], 0u);
}
```

```cpp
#include <cuda_runtime.h>
#include <cuda.h>
#include <stdint.h>

namespace {

constexpr int SEQ = 2048, DM = 576, FF = 4608;
constexpr int NSLOT = 9;
constexpr int SLOT = 8192;
constexpr int HS = 16384;
constexpr int RING = NSLOT * SLOT;
constexpr int OFF_WOR = 9 * HS;
constexpr int OFF_BAR = OFF_WOR + 4 * 2048;
constexpr int SMEM_BYTES = RING + OFF_BAR + 512;
constexpr int OFF_W24 = 0;
constexpr int OTILE = 128 * 144;
constexpr int OFF_OP = OTILE, OFF_WO0 = OTILE + 2048;
constexpr int OFF_AK = 6 * HS, OFF_AQ = OFF_AK + 8960, OFF_AV = 7 * HS;
constexpr int BAR_FULL = 0, BAR_EMPTY = 9, BAR_X = 18, BAR_WOR = 27, BAR_XDONE = 28, BAR_W24 = 29, BAR_QST = 30, BAR_WOF = 31, BAR_WOE = 33,
              BAR_ATI = 35, BAR_ATD = 37, BAR_O = 39, BAR_OFREE = 40;
constexpr int SPIN_LIMIT = 1 << 20;

__device__ uint4 g_qkv[216 * SEQ];
__device__ uint32_t g_o[128 * 128 * 36];
__device__ unsigned g_cnt[16 * 32];
__device__ unsigned g_done;
__device__ unsigned g_epoch;

__device__ __forceinline__ uint32_t smem_u32(const void* p) { return (uint32_t)__cvta_generic_to_shared(p); }
__device__ __forceinline__ void wg_fence() { asm volatile("wgmma.fence.sync.aligned;\n" ::: "memory"); }
__device__ __forceinline__ void wg_commit() { asm volatile("wgmma.commit_group.sync.aligned;\n" ::: "memory"); }
template <int N> __device__ __forceinline__ void wg_wait() { asm volatile("wgmma.wait_group.sync.aligned %0;\n" ::"n"(N) : "memory"); }
__device__ __forceinline__ void mbar_init(uint32_t a, int c) { asm volatile("mbarrier.init.shared::cta.b64 [%0], %1;" ::"r"(a), "r"(c) : "memory"); }
__device__ __forceinline__ void mbar_expect(uint32_t a, uint32_t b) { asm volatile("mbarrier.arrive.expect_tx.shared::cta.b64 _, [%0], %1;" ::"r"(a), "r"(b) : "memory"); }
__device__ __forceinline__ void mbar_arrive(uint32_t a) { asm volatile("mbarrier.arrive.shared::cta.b64 _, [%0];" ::"r"(a) : "memory"); }
__device__ __forceinline__ uint32_t mbar_try(uint32_t a, uint32_t par) {
  uint32_t ok;
  asm volatile("{\n.reg .pred p;\nmbarrier.try_wait.parity.shared::cta.b64 p, [%1], %2;\nselp.u32 %0,1,0,p;\n}\n" : "=r"(ok) : "r"(a), "r"(par) : "memory");
  return ok;
}
__device__ __forceinline__ void mbar_wait(uint32_t a, uint32_t par) {
  int it = 0;
  while (true) {
    if (mbar_try(a, par)) break;
    if (++it > SPIN_LIMIT) __trap();
  }
}
__device__ __forceinline__ void fence_mbar_init() { asm volatile("fence.mbarrier_init.release.cluster;" ::: "memory"); }
__device__ __forceinline__ void fence_async_smem() { asm volatile("fence.proxy.async.shared::cta;\n" ::: "memory"); }
__device__ __forceinline__ void fence_async_gmem() { asm volatile("fence.proxy.async.global;\n" ::: "memory"); }
__device__ __forceinline__ void tma2d(uint32_t dst, const CUtensorMap* m, int c0, int c1, uint32_t bar) {
  asm volatile("cp.async.bulk.tensor.2d.shared::cluster.global.mbarrier::complete_tx::bytes [%0], [%1, {%3, %4}], [%2];" ::"r"(dst), "l"(m), "r"(bar), "r"(c0), "r"(c1) : "memory");
}
__device__ __forceinline__ void bulk_g2s(uint32_t dst, const void* src, uint32_t bytes, uint32_t bar) {
  asm volatile("cp.async.bulk.shared::cluster.global.mbarrier::complete_tx::bytes [%0], [%1], %2, [%3];" ::"r"(dst), "l"(src), "r"(bytes), "r"(bar) : "memory");
}
__device__ __forceinline__ void tma2d_store(const CUtensorMap* m, uint32_t src, int c0, int c1) {
  asm volatile("cp.async.bulk.tensor.2d.global.shared::cta.tile.bulk_group [%0, {%2, %3}], [%1];" ::"l"(m), "r"(src), "r"(c0), "r"(c1) : "memory");
}
__device__ __forceinline__ bool elect() {
  uint32_t p;
  asm volatile("{\n.reg .pred p;\nelect.sync _|p, 0xffffffff;\nselp.u32 %0, 1, 0, p;\n}\n" : "=r"(p));
  return p;
}
__device__ __forceinline__ void tma2d_red(const CUtensorMap* m, uint32_t src, int c0, int c1) {
  asm volatile("cp.reduce.async.bulk.tensor.2d.global.shared::cta.add.tile.bulk_group [%0, {%2, %3}], [%1];" ::"l"(m), "r"(src), "r"(c0), "r"(c1) : "memory");
}
__device__ __forceinline__ void bulk_commit() { asm volatile("cp.async.bulk.commit_group;" ::: "memory"); }
__device__ __forceinline__ void bulk_wait_all() { asm volatile("cp.async.bulk.wait_group 0;" ::: "memory"); }
__device__ __forceinline__ void bulk_wait_read_all() { asm volatile("cp.async.bulk.wait_group.read 0;" ::: "memory"); }
__device__ __forceinline__ void ldsm4(uint32_t addr, uint32_t& r0, uint32_t& r1, uint32_t& r2, uint32_t& r3) {
  asm volatile("ldmatrix.sync.aligned.m8n8.x4.shared.b16 {%0,%1,%2,%3}, [%4];" : "=r"(r0), "=r"(r1), "=r"(r2), "=r"(r3) : "r"(addr) : "memory");
}
__device__ __forceinline__ void ldsm4_tied(uint32_t zero, uint32_t addr, uint32_t& r0, uint32_t& r1, uint32_t& r2, uint32_t& r3) {
  asm volatile("{\n.reg .pred p;\nsetp.eq.u32 p, %5, 0;\n@p ldmatrix.sync.aligned.m8n8.x4.shared.b16 {%0,%1,%2,%3}, [%4];\n}\n"
               : "+r"(r0), "+r"(r1), "+r"(r2), "+r"(r3) : "r"(addr), "r"(zero) : "memory");
}
__device__ __forceinline__ void stsm4(uint32_t addr, uint32_t r0, uint32_t r1, uint32_t r2, uint32_t r3) {
  asm volatile("stmatrix.sync.aligned.m8n8.x4.shared.b16 [%0], {%1,%2,%3,%4};" ::"r"(addr), "r"(r0), "r"(r1), "r"(r2), "r"(r3) : "memory");
}
template <int N> __device__ __forceinline__ void lds(uint32_t addr, uint32_t* v) {
  if (N == 4) asm volatile("ld.shared.v4.b32 {%0,%1,%2,%3}, [%4];" : "=r"(v[0]), "=r"(v[1]), "=r"(v[2]), "=r"(v[3]) : "r"(addr));
  else if (N == 2) asm volatile("ld.shared.v2.b32 {%0,%1}, [%2];" : "=r"(v[0]), "=r"(v[1]) : "r"(addr));
  else asm volatile("ld.shared.b32 %0, [%1];" : "=r"(v[0]) : "r"(addr));
}
__device__ __forceinline__ uint32_t pack2(float lo, float hi) { uint32_t r; asm("cvt.rn.bf16x2.f32 %0, %1, %2;" : "=r"(r) : "f"(hi), "f"(lo)); return r; }
__device__ __forceinline__ float bf_lo(uint32_t v) { return __uint_as_float(v << 16); }
__device__ __forceinline__ float bf_hi(uint32_t v) { return __uint_as_float(v & 0xffff0000u); }
__device__ __forceinline__ uint32_t bsub2(uint32_t a, uint32_t b) { uint32_t r; asm("sub.rn.bf16x2 %0, %1, %2;" : "=r"(r) : "r"(a), "r"(b)); return r; }
__device__ __forceinline__ uint32_t bmul2(uint32_t a, uint32_t b) { uint32_t r; asm("mul.rn.bf16x2 %0, %1, %2;" : "=r"(r) : "r"(a), "r"(b)); return r; }
__device__ __forceinline__ float tanh_hw(float x) { float y; asm("tanh.approx.f32 %0, %1;" : "=f"(y) : "f"(x)); return y; }
__device__ __forceinline__ float ex2(float x) { float y; asm("ex2.approx.ftz.f32 %0, %1;" : "=f"(y) : "f"(x)); return y; }
__device__ __forceinline__ unsigned ld_acquire(const unsigned* p) { unsigned v; asm volatile("ld.acquire.gpu.global.u32 %0, [%1];" : "=r"(v) : "l"(p) : "memory"); return v; }
__device__ __forceinline__ void red_release(unsigned* p, unsigned v) { asm volatile("red.release.gpu.global.add.u32 [%0], %1;" ::"l"(p), "r"(v) : "memory"); }
__device__ __forceinline__ void wait_counter(const unsigned* p, unsigned target) {
  int it = 0;
  while ((int)(ld_acquire(p) - target) < 0) { __nanosleep(128); if (++it > SPIN_LIMIT) __trap(); }
}
__device__ __forceinline__ void mma16816(float (&d)[4], uint32_t a0, uint32_t a1, uint32_t a2, uint32_t a3, uint32_t b0, uint32_t b1) {
  asm volatile("mma.sync.aligned.m16n8k16.row.col.f32.bf16.bf16.f32 {%0,%1,%2,%3}, {%4,%5,%6,%7}, {%8,%9}, {%0,%1,%2,%3};"
               : "+f"(d[0]), "+f"(d[1]), "+f"(d[2]), "+f"(d[3]) : "r"(a0), "r"(a1), "r"(a2), "r"(a3), "r"(b0), "r"(b1));
}
__device__ __forceinline__ void mma1688(float (&d)[4], uint32_t a0, uint32_t a1, uint32_t b0) {
  asm volatile("mma.sync.aligned.m16n8k8.row.col.f32.bf16.bf16.f32 {%0,%1,%2,%3}, {%4,%5}, {%6}, {%0,%1,%2,%3};"
               : "+f"(d[0]), "+f"(d[1]), "+f"(d[2]), "+f"(d[3]) : "r"(a0), "r"(a1), "r"(b0));
}

template <int NA> __device__ __forceinline__ void wgmma_rs_n64(float (&d)[NA], uint32_t a0, uint32_t a1, uint32_t a2, uint32_t a3, uint64_t db, int sd) {
  asm volatile("{\n.reg .pred p;\nsetp.ne.b32 p, %37, 0;\n"
    "wgmma.mma_async.sync.aligned.m64n64k16.f32.bf16.bf16 {%0, %1, %2, %3, %4, %5, %6, %7, %8, %9, %10, %11, %12, %13, %14, %15, %16, %17, %18, %19, %20, %21, %22, %23, %24, %25, %26, %27, %28, %29, %30, %31}, {%32, %33, %34, %35}, %36, p, 1, 1, 1;\n"
    "}\n"
    : "+f"(d[0]), "+f"(d[1]), "+f"(d[2]), "+f"(d[3]), "+f"(d[4]), "+f"(d[5]), "+f"(d[6]), "+f"(d[7]), "+f"(d[8]), "+f"(d[9]), "+f"(d[10]), "+f"(d[11]), "+f"(d[12]), "+f"(d[13]), "+f"(d[14]), "+f"(d[15]), "+f"(d[16]), "+f"(d[17]), "+f"(d[18]), "+f"(d[19]), "+f"(d[20]), "+f"(d[21]), "+f"(d[22]), "+f"(d[23]), "+f"(d[24]), "+f"(d[25]), "+f"(d[26]), "+f"(d[27]), "+f"(d[28]), "+f"(d[29]), "+f"(d[30]), "+f"(d[31])
    : "r"(a0), "r"(a1), "r"(a2), "r"(a3), "l"(db), "r"(sd));
}

template <int NA> __device__ __forceinline__ void wgmma_ss_n64(float (&d)[NA], uint64_t da, uint64_t db, int sd) {
  asm volatile("{\n.reg .pred p;\nsetp.ne.b32 p, %34, 0;\n"
    "wgmma.mma_async.sync.aligned.m64n64k16.f32.bf16.bf16 {%0, %1, %2, %3, %4, %5, %6, %7, %8, %9, %10, %11, %12, %13, %14, %15, %16, %17, %18, %19, %20, %21, %22, %23, %24, %25, %26, %27, %28, %29, %30, %31}, %32, %33, p, 1, 1, 0, 1;\n"
    "}\n"
    : "+f"(d[0]), "+f"(d[1]), "+f"(d[2]), "+f"(d[3]), "+f"(d[4]), "+f"(d[5]), "+f"(d[6]), "+f"(d[7]), "+f"(d[8]), "+f"(d[9]), "+f"(d[10]), "+f"(d[11]), "+f"(d[12]), "+f"(d[13]), "+f"(d[14]), "+f"(d[15]), "+f"(d[16]), "+f"(d[17]), "+f"(d[18]), "+f"(d[19]), "+f"(d[20]), "+f"(d[21]), "+f"(d[22]), "+f"(d[23]), "+f"(d[24]), "+f"(d[25]), "+f"(d[26]), "+f"(d[27]), "+f"(d[28]), "+f"(d[29]), "+f"(d[30]), "+f"(d[31])
    : "l"(da), "l"(db), "r"(sd));
}

template <int NA> __device__ __forceinline__ void wgmma_rs_n88(float (&d)[NA], uint32_t a0, uint32_t a1, uint32_t a2, uint32_t a3, uint64_t db, int sd) {
  asm volatile("{\n.reg .pred p;\nsetp.ne.b32 p, %49, 0;\n"
    "wgmma.mma_async.sync.aligned.m64n88k16.f32.bf16.bf16 {%0, %1, %2, %3, %4, %5, %6, %7, %8, %9, %10, %11, %12, %13, %14, %15, %16, %17, %18, %19, %20, %21, %22, %23, %24, %25, %26, %27, %28, %29, %30, %31, %32, %33, %34, %35, %36, %37, %38, %39, %40, %41, %42, %43}, {%44, %45, %46, %47}, %48, p, 1, 1, 1;\n"
    "}\n"
    : "+f"(d[0]), "+f"(d[1]), "+f"(d[2]), "+f"(d[3]), "+f"(d[4]), "+f"(d[5]), "+f"(d[6]), "+f"(d[7]), "+f"(d[8]), "+f"(d[9]), "+f"(d[10]), "+f"(d[11]), "+f"(d[12]), "+f"(d[13]), "+f"(d[14]), "+f"(d[15]), "+f"(d[16]), "+f"(d[17]), "+f"(d[18]), "+f"(d[19]), "+f"(d[20]), "+f"(d[21]), "+f"(d[22]), "+f"(d[23]), "+f"(d[24]), "+f"(d[25]), "+f"(d[26]), "+f"(d[27]), "+f"(d[28]), "+f"(d[29]), "+f"(d[30]), "+f"(d[31]), "+f"(d[32]), "+f"(d[33]), "+f"(d[34]), "+f"(d[35]), "+f"(d[36]), "+f"(d[37]), "+f"(d[38]), "+f"(d[39]), "+f"(d[40]), "+f"(d[41]), "+f"(d[42]), "+f"(d[43])
    : "r"(a0), "r"(a1), "r"(a2), "r"(a3), "l"(db), "r"(sd));
}

template <int NA> __device__ __forceinline__ void wgmma_ss_n88(float (&d)[NA], uint64_t da, uint64_t db, int sd) {
  asm volatile("{\n.reg .pred p;\nsetp.ne.b32 p, %46, 0;\n"
    "wgmma.mma_async.sync.aligned.m64n88k16.f32.bf16.bf16 {%0, %1, %2, %3, %4, %5, %6, %7, %8, %9, %10, %11, %12, %13, %14, %15, %16, %17, %18, %19, %20, %21, %22, %23, %24, %25, %26, %27, %28, %29, %30, %31, %32, %33, %34, %35, %36, %37, %38, %39, %40, %41, %42, %43}, %44, %45, p, 1, 1, 0, 1;\n"
    "}\n"
    : "+f"(d[0]), "+f"(d[1]), "+f"(d[2]), "+f"(d[3]), "+f"(d[4]), "+f"(d[5]), "+f"(d[6]), "+f"(d[7]), "+f"(d[8]), "+f"(d[9]), "+f"(d[10]), "+f"(d[11]), "+f"(d[12]), "+f"(d[13]), "+f"(d[14]), "+f"(d[15]), "+f"(d[16]), "+f"(d[17]), "+f"(d[18]), "+f"(d[19]), "+f"(d[20]), "+f"(d[21]), "+f"(d[22]), "+f"(d[23]), "+f"(d[24]), "+f"(d[25]), "+f"(d[26]), "+f"(d[27]), "+f"(d[28]), "+f"(d[29]), "+f"(d[30]), "+f"(d[31]), "+f"(d[32]), "+f"(d[33]), "+f"(d[34]), "+f"(d[35]), "+f"(d[36]), "+f"(d[37]), "+f"(d[38]), "+f"(d[39]), "+f"(d[40]), "+f"(d[41]), "+f"(d[42]), "+f"(d[43])
    : "l"(da), "l"(db), "r"(sd));
}


__device__ __forceinline__ uint64_t mkd(uint32_t lo) { return ((uint64_t)0x40000040u << 32) | (uint64_t)lo; }

constexpr uint32_t sr = 1024, sb = sr + RING;
constexpr uint32_t bars = sb + OFF_BAR;
constexpr uint32_t RING_LO = (sr >> 4) | (512u << 16);

template <int NA> __device__ __forceinline__ void acc_fence(float (&d)[NA]) {
  asm volatile("" : "+f"(d[0]), "+f"(d[1]), "+f"(d[2]), "+f"(d[3]), "+f"(d[4]), "+f"(d[5]), "+f"(d[6]), "+f"(d[7]), "+f"(d[8]), "+f"(d[9]), "+f"(d[10]), "+f"(d[11]), "+f"(d[12]), "+f"(d[13]), "+f"(d[14]), "+f"(d[15]), "+f"(d[16]), "+f"(d[17]), "+f"(d[18]), "+f"(d[19]), "+f"(d[20]), "+f"(d[21]), "+f"(d[22]), "+f"(d[23]), "+f"(d[24]), "+f"(d[25]), "+f"(d[26]), "+f"(d[27]), "+f"(d[28]), "+f"(d[29]), "+f"(d[30]), "+f"(d[31]) :: "memory");
}

template <int V> struct IC { static constexpr int value = V; };

template <int PH, bool FIRST, int NA, class M, class F>
__device__ __forceinline__ void run_pass(float (&other)[NA], M&& mma, F&& slice) {
#pragma unroll
  for (int s = 0; s < 9; s++) {
    wg_fence();
    mma(s, RING_LO + s * (SLOT >> 4));
    wg_commit();
    mbar_wait(bars + (BAR_FULL + (s + 1) % 9) * 8, s < 8 ? PH : PH ^ 1);
    slice(s);
    wg_wait<1>();
    if (s == 0) acc_fence(other);
    if ((s || !FIRST) && (threadIdx.x & 127) == 0) mbar_arrive(bars + (BAR_EMPTY + (s + 8) % 9) * 8);
  }
}

template <int BUF, int PH, bool FIRST, int NA, class M, class F>
__device__ __forceinline__ void run_down(uint32_t wpar, bool last, float (&other)[NA], M&& mma, F&& slice) {
#pragma unroll
  for (int s = 0; s < 10; s++) {
    wg_fence();
    mma(s, s < 9 ? RING_LO + s * (SLOT >> 4) : ((sb + 8 * HS + BUF * SLOT) >> 4) | (512u << 16));
    wg_commit();
    if (s < 8) mbar_wait(bars + (BAR_FULL + s + 1) * 8, PH);
    else if (s == 8) mbar_wait(bars + (BAR_WOF + BUF) * 8, wpar);
    else if (!last) mbar_wait(bars + BAR_FULL * 8, PH ^ 1);
    slice(s);
    wg_wait<1>();
    if (s == 0) acc_fence(other);
    if ((threadIdx.x & 127) == 0) {
      if (s) mbar_arrive(bars + (BAR_EMPTY + s - 1) * 8);
      else {
        if (FIRST) { mbar_arrive(bars + (BAR_EMPTY + 8) * 8); mbar_arrive(bars + (BAR_WOE + BUF) * 8); }
        mbar_arrive(bars + (BAR_WOE + (BUF ^ 1)) * 8);
      }
    }
  }
}

struct Maps {
  CUtensorMap x, wqkv, w24, wg, wu, wd, woa, wob, out, lkv, lq, op;
};

__global__ void __launch_bounds__(384, 1)
fused_kernel(const __grid_constant__ Maps mp, const void* __restrict__ wqkv, uint32_t zero) {
  extern __shared__ __align__(1024) uint8_t smem[];
  const int j = (blockIdx.x >> 2) & 7, m = (blockIdx.x & 3) + ((blockIdx.x >> 3) & 12);
  const int m0 = m * 128;
  if (threadIdx.x == 256) {
#pragma unroll
    for (int i = 0; i < 9; i++) {
      const uint32_t b = bars + (BAR_X + i) * 8;
      mbar_init(b, 1);
      fence_mbar_init();
      mbar_expect(b, HS);
      tma2d(sb + i * HS, &mp.x, i * 64, m0, b);
    }
  }
  const int warp = __shfl_sync(0xffffffffu, threadIdx.x >> 5, 0), lane = threadIdx.x & 31;

  asm volatile("" ::: "memory");
  if (lane == 0) {
    if (warp == 9) {
      if (smem_u32(smem) != sr) __trap();
      for (int i = 0; i < NSLOT; i++) { mbar_init(bars + (BAR_FULL + i) * 8, 1); mbar_init(bars + (BAR_EMPTY + i) * 8, 2); }
      fence_mbar_init();
    } else if (warp == 10) {
      mbar_init(bars + BAR_WOR * 8, 1);
      mbar_init(bars + BAR_XDONE * 8, 9);
      mbar_init(bars + BAR_W24 * 8, 1);
      mbar_init(bars + BAR_QST * 8, 8);
      for (int i = 0; i < 2; i++) { mbar_init(bars + (BAR_WOF + i) * 8, 1); mbar_init(bars + (BAR_WOE + i) * 8, 2); }
      for (int i = 0; i < 2; i++) { mbar_init(bars + (BAR_ATI + i) * 8, 1); mbar_init(bars + (BAR_ATD + i) * 8, 1); }
      mbar_init(bars + BAR_O * 8, 1);
      mbar_init(bars + BAR_OFREE * 8, 8);
      fence_mbar_init();
    }
  }
  __syncthreads();

  if (warp < 8) {
    asm volatile("setmaxnreg.inc.sync.aligned.u32 232;\n");
    const int wg = warp >> 2;
    const int lrow = (warp & 3) * 16 + (lane & 15);
    const uint32_t rowa = sb + wg * 8192 + lrow * 128;
    const uint32_t swz = ((lane >> 4) ^ (lrow & 7)) << 4;
    uint32_t adr[4];
#pragma unroll
    for (int i = 0; i < 4; i++) { adr[i] = rowa + (swz ^ (i << 5)); asm volatile("" : "+r"(adr[i])); }
    uint32_t a[128];
    uint32_t sg[16], oq[4], oz[4];
    float accA[32], accB[44];
    float rs0, rs1, rh0, rh1;
    uint32_t mp0, mp1;
    {
      float cs[2][4] = {}, c1[2][4] = {}, c2[2][4] = {};
      mbar_wait(bars + BAR_X * 8, 0);
#pragma unroll
      for (int kb = 0; kb < 9; kb++) {
        uint32_t ok = 1;
        if (kb < 8) ok = mbar_try(bars + (BAR_X + kb + 1) * 8, 0);
        uint32_t* r = (kb < 8) ? &a[kb * 16] : sg;
#pragma unroll
        for (int kk = 0; kk < 4; kk++) ldsm4(adr[kk] + kb * HS, r[kk * 4], r[kk * 4 + 1], r[kk * 4 + 2], r[kk * 4 + 3]);
#pragma unroll
        for (int kk = 0; kk < 4; kk++, r += 4) {
          mma16816(cs[kk & 1], r[0], r[1], r[2], r[3], 0x3f803f80u, 0x3f803f80u);
          mma1688(c1[0], r[0], r[1], r[0]);
          mma1688(c2[0], r[0], r[1], r[1]);
          mma1688(c1[1], r[2], r[3], r[2]);
          mma1688(c2[1], r[2], r[3], r[3]);
        }
        if (!ok) mbar_wait(bars + (BAR_X + kb + 1) * 8, 0);
      }
      __syncwarp();
      if (lane == 0) mbar_arrive(bars + BAR_XDONE * 8);
      const float mu0 = (cs[0][0] + cs[1][0]) * (1.f / DM), mu1 = (cs[0][2] + cs[1][2]) * (1.f / DM);
      mp0 = pack2(mu0, mu0); mp1 = pack2(mu1, mu1);
      rs0 = (lane & 4) ? c1[0][1] + c1[1][1] : c1[0][0] + c1[1][0];
      rs1 = (lane & 4) ? c2[0][3] + c2[1][3] : c2[0][2] + c2[1][2];
      rh0 = mu0 * mu0; rh1 = mu1 * mu1;
    }
    auto finish_rstd = [&]() {
      const int src = (lane & ~3) | (lane >> 3);
      rs0 = rsqrtf(fmaxf(__shfl_sync(0xffffffffu, rs0, src) * (1.f / DM) - rh0, 0.f) + 1e-5f);
      rs1 = rsqrtf(fmaxf(__shfl_sync(0xffffffffu, rs1, src) * (1.f / DM) - rh1, 0.f) + 1e-5f);
      rh0 = 0.5f * rs0; rh1 = 0.5f * rs1;
    };
    auto centre = [&](int kb) {
#pragma unroll
      for (int i = kb * 16; i < kb * 16 + 16; i++) a[i] = bsub2(a[i], (i & 1) ? mp1 : mp0);
    };
    centre(0);

    const uint32_t xlo = ((sb + 8 * HS + wg * 8192) >> 4) | (1u << 16);

    auto rs64 = [&](auto& acc, int kb, uint32_t blo, bool first) {
#pragma unroll
      for (int kk = 0; kk < 4; kk++)
        wgmma_rs_n64(acc, a[kb * 16 + kk * 4], a[kb * 16 + kk * 4 + 1], a[kb * 16 + kk * 4 + 2], a[kb * 16 + kk * 4 + 3], mkd(blo + kk * 128), !(first && kk == 0));
    };
    auto ss64 = [&](auto& acc, int slot, uint32_t blo) {
#pragma unroll
      for (int kk = 0; kk < 4; kk++) wgmma_ss_n64(acc, mkd(xlo - (8 - slot) * (HS >> 4) + kk * 2), mkd(blo + kk * 128), 1);
    };
    auto mma64 = [&](auto& acc, int s, uint32_t blo) { if (s < 8) rs64(acc, s, blo, s == 0); else ss64(acc, 8, blo); };
    char* qp = reinterpret_cast<char*>(g_qkv + (j * 24) * SEQ + m0 + (threadIdx.x >> 5) * 16) + (threadIdx.x & 31) * 4;
    auto qkv_store = [&](const auto& acc, int nb, int chunk) {
      *reinterpret_cast<uint32_t*>(qp + chunk * (SEQ * 16)) = pack2(acc[4 * nb] * rs0, acc[4 * nb + 1] * rs0);
      *reinterpret_cast<uint32_t*>(qp + chunk * (SEQ * 16) + 128) = pack2(acc[4 * nb + 2] * rs1, acc[4 * nb + 3] * rs1);
    };
    auto sig_slice = [&](const auto& acc, int s) {
      if (s >= 1) {
#pragma unroll
        for (int e = 2 * (s - 1); e < 2 * s; e++) {
          const float r = (e & 1) ? rh1 : rh0;
          sg[e] = pack2(fmaf(tanh_hw(acc[2 * e] * r), r, r), fmaf(tanh_hw(acc[2 * e + 1] * r), r, r));
        }
      }
    };
    auto h_val = [&](const auto& acc, int e) { return bmul2(sg[e], pack2(acc[2 * e], acc[2 * e + 1])); };
    auto load_h = [&](int pos) {
#pragma unroll
      for (int kk = (pos & 1) * 2; kk < (pos & 1) * 2 + 2; kk++) {
        const int kb = pos >> 1;
        ldsm4_tied(zero, adr[kk] + kb * HS, a[kb * 16 + kk * 4], a[kb * 16 + kk * 4 + 1], a[kb * 16 + kk * 4 + 2], a[kb * 16 + kk * 4 + 3]);
      }
    };

    mbar_wait(bars + BAR_FULL * 8, 0);
    run_pass<0, true>(accA, [&](int s, uint32_t b) { mma64(accB, s, b); }, [&](int s) {
      if (s < 7) centre(s + 1);
      if (s == 0) finish_rstd();
      if (s == 6) {
        mbar_wait(bars + BAR_XDONE * 8, 0);
#pragma unroll
        for (int i = 0; i < 16; i++) sg[i] = bsub2(sg[i], (i & 1) ? mp1 : mp0);
#pragma unroll
        for (int kk = 0; kk < 4; kk++) stsm4(adr[kk] + 8 * HS, sg[kk * 4], sg[kk * 4 + 1], sg[kk * 4 + 2], sg[kk * 4 + 3]);
        fence_async_smem();
      }
      if (s == 7) asm volatile("bar.sync %0, 128;" ::"r"(1 + wg) : "memory");
    });
    run_pass<1, false>(accB, [&](int s, uint32_t b) { mma64(accA, s, b); }, [&](int s) {
      if (s >= 1) qkv_store(accB, s - 1, s - 1);
      if (s == 8) mbar_wait(bars + BAR_W24 * 8, 0);
    });
    run_pass<0, false>(accA, [&](int s, uint32_t b) {
      const uint32_t lo = (b & 0xffffu) | (((OFF_W24 + RING) >> 4) << 16);
#pragma unroll
      for (int kk = 0; kk < 4; kk++) {
        const int k = s * 4 + kk;
        if (s < 8) wgmma_rs_n88(accB, a[k * 4], a[k * 4 + 1], a[k * 4 + 2], a[k * 4 + 3], mkd(lo + kk * 128), k != 0);
        else wgmma_ss_n88(accB, mkd(xlo + kk * 2), mkd(lo + kk * 128), 1);
      }
    }, [&](int s) { if (s >= 1) qkv_store(accA, s - 1, 7 + s); });
    run_pass<1, false>(accB, [&](int s, uint32_t b) { mma64(accA, s, b); }, [&](int s) {
      if (s == 1) asm volatile("" : "+f"(accB[32]), "+f"(accB[33]), "+f"(accB[34]), "+f"(accB[35]), "+f"(accB[36]), "+f"(accB[37]), "+f"(accB[38]),
                               "+f"(accB[39]), "+f"(accB[40]), "+f"(accB[41]), "+f"(accB[42]), "+f"(accB[43]) :: "memory");
      if (s >= 1 && s <= 4) { qkv_store(accB, 2 * s - 2, 14 + 2 * s); qkv_store(accB, 2 * s - 1, 15 + 2 * s); }
      if (s == 5) { qp += (192 - 21 * j) * (SEQ * 16); qkv_store(accB, 8, 0); qkv_store(accB, 9, 1); }
      if (s == 6) {
        qkv_store(accB, 10, 2);
        __syncwarp();
        if (lane == 0) mbar_arrive(bars + BAR_QST * 8);
      }
    });
    for (int c = 0; c < 8; c++) {
      run_pass<0, false>(accA, [&](int s, uint32_t b) { mma64(accB, s, b); }, [&](int s) { sig_slice(accA, s); });
      run_pass<1, false>(accB, [&](int s, uint32_t b) { mma64(accA, s, b); }, [&](int s) {
        if (s == 1 && c >= 6) mbar_wait(bars + (BAR_ATD - 6 + c) * 8, 0);
        if (s >= 1 && s <= 7 && (s & 1)) {
          const int t = s >> 1;
          stsm4(adr[t] + c * HS, h_val(accB, 4 * t), h_val(accB, 4 * t + 1), h_val(accB, 4 * t + 2), h_val(accB, 4 * t + 3));
        }
      });
    }
    run_pass<0, false>(accA, [&](int s, uint32_t b) { mma64(accB, s, b); }, [&](int s) {
      sig_slice(accA, s);
      if (s == 0) {
        fence_async_smem();
        asm volatile("bar.sync %0, 128;" ::"r"(1 + wg) : "memory");
      }
      if (s >= 2) load_h(s - 2);
      if (s == 6) {
        __syncwarp();
        if (lane == 0) mbar_arrive(bars + BAR_OFREE * 8);
      }
    });
    constexpr uint32_t worlo = ((sb + OFF_WOR) >> 4) | (512u << 16);
    const int grow = m0 + warp * 16;
    int blk = j;
    auto mmaD = [&](auto& acc, int s, uint32_t blo, const uint32_t* sh, uint32_t shlo) {
      if (s < 6) rs64(acc, s, blo, s == 0);
      else if (s < 8) ss64(acc, s, blo);
      else rs64(acc, s - 2, blo, false);
      if (s == 9 && sh) wgmma_rs_n64(acc, sh[0], sh[1], sh[2], sh[3], mkd(shlo), 1);
    };
    auto flush_store = [&](const auto& acc, int slot, int t) {
      stsm4(adr[t] + slot * HS, pack2(acc[8 * t], acc[8 * t + 1]), pack2(acc[8 * t + 2], acc[8 * t + 3]),
            pack2(acc[8 * t + 4], acc[8 * t + 5]), pack2(acc[8 * t + 6], acc[8 * t + 7]));
    };
    auto flush_issue = [&](int slot, int cb) {
      fence_async_smem();
      __syncwarp();
      if (elect()) { tma2d_red(&mp.out, sb + slot * HS + warp * 2048, cb * 64, grow); bulk_commit(); }
    };
    run_down<0, 1, true>(0, false, accB, [&](int s, uint32_t b) { mmaD(accA, s, b, oz, ((sb + OFF_WO0) >> 4) | (512u << 16)); }, [&](int s) {
      if (s < 5) load_h(7 + s);
      if (s >= 1 && s <= 4) {
#pragma unroll
        for (int e = 4 * (s - 1); e < 4 * s; e++) a[96 + e] = h_val(accB, e);
      }
      if (s == 7) {
        mbar_wait(bars + BAR_WOR * 8, 0);
        mbar_wait(bars + BAR_O * 8, 0);
        fence_async_gmem();
        const uint32_t orow = (threadIdx.x >> 5) * 16 + (threadIdx.x & 15), oa = sb + orow * 144, odd = j & 1;
#pragma unroll
        for (int kk = 0; kk < 4; kk++) ldsm4(oa + odd * 16 + kk * 32 + (threadIdx.x & 16), a[112 + kk * 4], a[113 + kk * 4], a[114 + kk * 4], a[115 + kk * 4]);
        ldsm4(((threadIdx.x >> 4) & 1) == odd ? oa + 128 - odd * 128 : sb + OFF_OP + orow * 16, oq[0], oq[1], oq[2], oq[3]);
#pragma unroll
        for (int i = 0; i < 4; i++) asm volatile("mul.lo.u32 %0, %1, %2;" : "=r"(oz[i]) : "r"(oq[i]), "r"(odd ^ 1));
      }
    });
    auto flush_slice = [&](const auto& acc, int slot, int cb, int s) {
      if (s == 0) { asm volatile("cp.async.bulk.wait_group.read 1;" ::: "memory"); __syncwarp(); }
      if (s >= 1 && s <= 4) flush_store(acc, slot, s - 1);
      if (s == 5) flush_issue(slot, cb);
    };
    for (int p = 1; p < 9; p += 2) {
      int pb = blk; blk = (blk == 8) ? 0 : blk + 1;
      run_down<1, 0, false>((p >> 1) & 1, false, accA, [&](int s, uint32_t b) { mmaD(accB, s, b, oq, worlo + (p >> 1) * 128); }, [&](int s) { flush_slice(accA, 2, pb, s); });
      pb = blk; blk = (blk == 8) ? 0 : blk + 1;
      if (p == 7 && wg == 1) asm volatile("bar.sync 5, 256;" ::: "memory");
      run_down<0, 1, false>(((p + 1) >> 1) & 1, p == 7, accB, [&](int s, uint32_t b) { mmaD(accA, s, b, nullptr, 0); }, [&](int s) {
        flush_slice(accB, 3, pb, s);
        if (s == 3 && p == 7 && wg == 0) asm volatile("bar.arrive 5, 256;" ::: "memory");
      });
    }
    flush_slice(accA, 2, blk, 0);
    wg_wait<0>();
    acc_fence(accA);
#pragma unroll
    for (int t = 1; t <= 5; t++) flush_slice(accA, 2, blk, t);
    bulk_wait_read_all();
  } else {
    asm volatile("setmaxnreg.dec.sync.aligned.u32 40;\n");
    if (warp == 8) {
      int st = 0; uint32_t ph = 1;
      auto stage = [&](const CUtensorMap* w, int c0, int c1) {
        mbar_wait(bars + (BAR_EMPTY + st) * 8, ph);
        const uint32_t fb = bars + (BAR_FULL + st) * 8;
        if (elect()) {
          mbar_expect(fb, SLOT);
          tma2d(sr + st * SLOT, w, c0, c1, fb);
        }
        st++;
        if (st == NSLOT) { st = 0; ph ^= 1; }
      };
      int blk = j;
#pragma unroll 1
      for (int p = 0; p < 30; p++) {
        const CUtensorMap* w; int c0, c1 = 0;
        if (p < 3) { w = &mp.wqkv; c0 = j * 192 + p * 64; }
        else if (p < 21) { w = (p & 1) ? &mp.wg : &mp.wu; c0 = j * 576 + ((p - 3) >> 1) * 64; }
        else { w = &mp.wd; c0 = blk * 64; c1 = j * 576; }
#pragma unroll 1
        for (int kb = 0; kb < 9; kb++) {
          stage(w, c0, c1 + kb * 64);
        }
        if (p >= 21) {
          const int q = p - 21;
          mbar_wait(bars + (BAR_WOE + (q & 1)) * 8, (q >> 1) & 1);
          if (elect()) {
            mbar_expect(bars + (BAR_WOF + (q & 1)) * 8, SLOT);
            tma2d(sb + 8 * HS + (q & 1) * SLOT, &mp.woa, c0, j * 72 + (j & 1) * 8, bars + (BAR_WOF + (q & 1)) * 8);
          }
          blk = (blk == 8) ? 0 : blk + 1;
        }
      }
    } else {
      const int aw = warp - 9;
      if (aw == 2 && elect()) {
        const CUtensorMap* mm = &mp.w24;
#pragma unroll 1
        for (int i = 0; i < 10; i++) asm volatile("prefetch.tensormap [%0];" ::"l"(mm + i) : "memory");
      }
      const unsigned target = (*(volatile unsigned*)&g_epoch + 1) * 8;
      if (aw == 1) {
#pragma unroll 1
        for (int kb = 0; kb < 9; kb++) {
          mbar_wait(bars + (BAR_X + kb) * 8, 0);
          if (elect()) tma2d_store(&mp.out, sb + kb * HS + j * 2048, kb * 64, m0 + j * 16);
        }
        if (elect()) bulk_commit();
        bulk_wait_read_all();
        __syncwarp();
        if (lane == 0) mbar_arrive(bars + BAR_XDONE * 8);
      }
      mbar_wait(bars + (BAR_X + 4) * 8, 0);
      for (int u = aw * 32 + lane; u < 36 * 4; u += 96) {
        const int r = m * 36 + (u >> 2), c = u & 3;
        asm volatile("prefetch.global.L2 [%0];" ::"l"(reinterpret_cast<const char*>(wqkv) + (size_t)r * (3 * DM * 2) + (c < 3 ? j * 384 + c * 128 : 3072 + j * 48)));
      }
      if (aw == 2) {
        mbar_wait(bars + BAR_XDONE * 8, 0);
        if (elect()) { mbar_expect(bars + BAR_W24 * 8, 9 * 64 * 48); mbar_expect(bars + BAR_WOR * 8, 4 * 2048); }
#pragma unroll 1
        for (int b = 0; b < 13; b++) {
          if (elect()) {
            if (b < 9) tma2d(sb + OFF_W24 + b * SLOT, &mp.w24, 1536 + j * 24, b * 64, bars + BAR_W24 * 8);
            else tma2d(sb + OFF_WOR + (b - 9) * 2048, &mp.wob, ((j + 2 * b - 17) % 9) * 64, (j & ~1) * 72 + 64, bars + BAR_WOR * 8);
          }
          __nanosleep(64);
        }
      }
      if (aw == 1) bulk_wait_all();
      asm volatile("bar.sync 3, 96;" ::: "memory");
      auto load_kq = [&](int t) {
        const int r2 = (m0 + t * 48) * 2;
        mbar_expect(bars + BAR_ATI * 8, 9 * (62 + 50) * 16);
        tma2d(sb + OFF_AK, &mp.lkv, r2 - 28, 72 + j * 9, bars + BAR_ATI * 8);
        tma2d(sb + OFF_AQ, &mp.lq, r2, j * 9, bars + BAR_ATI * 8);
      };
      auto load_v = [&](int t) {
        mbar_expect(bars + (BAR_ATI + 1) * 8, 9 * 62 * 16);
        tma2d(sb + OFF_AV, &mp.lkv, (m0 + t * 48) * 2 - 28, 144 + j * 9, bars + (BAR_ATI + 1) * 8);
      };
      if (aw == 0) {
        mbar_wait(bars + BAR_QST * 8, 0);
        if (lane == 0) red_release(&g_cnt[m * 32], 1);
        if (lane < 2) wait_counter(&g_cnt[(lane && m ? m - 1 : m) * 32], target);
        __syncwarp();
        fence_async_gmem();
        if (elect()) { load_kq(0); load_v(0); }
      }
      uint32_t l16 = (aw * 16 + (lane & 1) + (lane & 2) * 2 + (lane >> 4) * 8) * 16;
      auto fresh = [&]() { asm volatile("" : "+r"(l16)); return l16; };
      const float sc = 0.23570226039551584f * 1.4426950408889634f;
#pragma unroll 1
      for (int t = 0; t < 3; t++) {
        const bool active = t < 2 || aw < 2;
        float p0[8] = {}, p1[8] = {};
        uint32_t h8 = (threadIdx.x & 12) * 2;
        asm volatile("" : "+r"(h8));
        const uint32_t po = (0x70482800u >> h8) & 255, po3 = (0x6C682420u >> h8) & 255;
        const uint32_t px = (0x00100000u >> h8) & 255;
        mbar_wait(bars + BAR_ATI * 8, t & 1);
        if (active) {
          auto qk = [&](auto nw, uint32_t b) {
            constexpr int N = decltype(nw)::value;
            uint32_t u[N]; float q0[2 * N], q1[2 * N];
            const uint32_t o = fresh() + (b & 15), qa = o + (b >> 4) * 800 + (sb + OFF_AQ), ka = o + (b >> 4) * 992 + (sb + OFF_AK);
            lds<N>(qa, u);
#pragma unroll
            for (int i = 0; i < N; i++) { q0[2 * i] = bf_lo(u[i]); q0[2 * i + 1] = bf_hi(u[i]); }
            lds<N>(qa + 32, u);
#pragma unroll
            for (int i = 0; i < N; i++) { q1[2 * i] = bf_lo(u[i]); q1[2 * i + 1] = bf_hi(u[i]); }
#pragma unroll
            for (int s = 0; s < 9; s++) {
              lds<N>(ka + (16 - 2 * s) * 16, u);
#pragma unroll
              for (int i = 0; i < N; i++) {
                const float lo = bf_lo(u[i]), hi = bf_hi(u[i]);
                if (s < 8) { p1[s] = fmaf(q1[2 * i], lo, p1[s]); p1[s] = fmaf(q1[2 * i + 1], hi, p1[s]); }
                if (s > 0) { p0[s - 1] = fmaf(q0[2 * i], lo, p0[s - 1]); p0[s - 1] = fmaf(q0[2 * i + 1], hi, p0[s - 1]); }
              }
            }
          };
#pragma unroll 1
          for (int i = 0; i < 4; i++) qk(IC<2>(), po + ((8 * i) ^ px));
          qk(IC<1>(), po3);
        }
        asm volatile("bar.sync 3, 96;" ::: "memory");
        if (aw == 0 && elect()) { if (t < 2) load_kq(t + 1); else mbar_arrive(bars + BAR_ATD * 8); }
        if (active) {
          if (m0 + t == 0) {
            const int row = fresh() >> 4;
#pragma unroll
            for (int w = 1; w < 8; w++) { if (row < 2 * w) p0[w] = -INFINITY; if (row + 2 < 2 * w) p1[w] = -INFINITY; }
          }
          auto softmax = [&](float (&p)[8]) {
            const float mx = fmaxf(fmaxf(fmaxf(p[0], p[1]), fmaxf(p[2], p[3])), fmaxf(fmaxf(p[4], p[5]), fmaxf(p[6], p[7])));
            float l = 0.f;
#pragma unroll
            for (int w = 0; w < 8; w++) { p[w] = ex2((p[w] - mx) * sc); l += p[w]; }
            l = __fdividef(1.f, l);
#pragma unroll
            for (int w = 0; w < 8; w++) p[w] *= l;
          };
          softmax(p0); softmax(p1);
        }
        mbar_wait(bars + (BAR_ATI + 1) * 8, t & 1);
        if (active) {
          char* op = reinterpret_cast<char*>(g_o + (blockIdx.x * 128 + t * 48) * 36) + fresh() * 9;
          auto pv = [&](auto nw, uint32_t b) {
            constexpr int N = decltype(nw)::value;
            uint32_t u[N]; float o0[2 * N] = {}, o1[2 * N] = {};
            const uint32_t va = fresh() + (b & 15) + (b >> 4) * 992 + (sb + OFF_AV);
#pragma unroll
            for (int s = 0; s < 9; s++) {
              lds<N>(va + (16 - 2 * s) * 16, u);
#pragma unroll
              for (int i = 0; i < N; i++) {
                const float lo = bf_lo(u[i]), hi = bf_hi(u[i]);
                if (s < 8) { o1[2 * i] = fmaf(p1[s], lo, o1[2 * i]); o1[2 * i + 1] = fmaf(p1[s], hi, o1[2 * i + 1]); }
                if (s > 0) { o0[2 * i] = fmaf(p0[s - 1], lo, o0[2 * i]); o0[2 * i + 1] = fmaf(p0[s - 1], hi, o0[2 * i + 1]); }
              }
            }
            if (N == 2) {
              *reinterpret_cast<uint2*>(op + b) = make_uint2(pack2(o0[0], o0[1]), pack2(o0[2 % (2 * N)], o0[3 % (2 * N)]));
              *reinterpret_cast<uint2*>(op + b + 288) = make_uint2(pack2(o1[0], o1[1]), pack2(o1[2 % (2 * N)], o1[3 % (2 * N)]));
            } else {
              *reinterpret_cast<uint32_t*>(op + b) = pack2(o0[0], o0[1]);
              *reinterpret_cast<uint32_t*>(op + b + 288) = pack2(o1[0], o1[1]);
            }
          };
#pragma unroll 1
          for (int i = 0; i < 4; i++) pv(IC<2>(), po + ((8 * i) ^ px));
          pv(IC<1>(), po3);
        }
        asm volatile("bar.sync 3, 96;" ::: "memory");
        if (aw == 0 && elect()) { if (t < 2) load_v(t + 1); else mbar_arrive(bars + (BAR_ATD + 1) * 8); }
      }
      if (aw == 0) {
        if (elect()) {
          red_release(&g_cnt[m * 32 + 8 + (j >> 1)], 1);
          wait_counter(&g_cnt[m * 32 + 8 + (j >> 1)], (*(volatile unsigned*)&g_epoch + 1) * 2);
        }
        __syncwarp();
        mbar_wait(bars + BAR_OFREE * 8, 0);
        fence_async_gmem();
        if (elect()) {
          mbar_expect(bars + BAR_O * 8, OTILE + 4096);
          bulk_g2s(sb, g_o + blockIdx.x * 128 * 36, OTILE, bars + BAR_O * 8);
          tma2d(sb + OFF_OP, &mp.op, (j & 1) * 16, (blockIdx.x ^ 4) * 128, bars + BAR_O * 8);
          tma2d(sb + OFF_WO0, &mp.wob, j * 64, (j & ~1) * 72 + 64, bars + BAR_O * 8);
          if (atomicInc(&g_done, 127u) == 127u) atomicAdd(&g_epoch, 1u);
        }
      }
    }
  }
}

typedef CUresult (*EncodeFn)(CUtensorMap*, CUtensorMapDataType, cuuint32_t, void*, const cuuint64_t*, const cuuint64_t*, const cuuint32_t*,
                             const cuuint32_t*, CUtensorMapInterleave, CUtensorMapSwizzle, CUtensorMapL2promotion, CUtensorMapFloatOOBfill);

void encode2(EncodeFn fn, CUtensorMap* m, const void* p, uint64_t cols, uint64_t rows, uint32_t bc, uint32_t br, bool raw = false,
             CUtensorMapL2promotion promo = CU_TENSOR_MAP_L2_PROMOTION_L2_128B) {
  const cuuint64_t d[2] = {cols, rows}, s[1] = {cols * (raw ? 8 : 2)};
  const cuuint32_t b[2] = {bc, br}, es[2] = {1, 1};
  fn(m, raw ? CU_TENSOR_MAP_DATA_TYPE_UINT64 : CU_TENSOR_MAP_DATA_TYPE_BFLOAT16, 2, const_cast<void*>(p), d, s, b, es, CU_TENSOR_MAP_INTERLEAVE_NONE,
     raw ? CU_TENSOR_MAP_SWIZZLE_NONE : CU_TENSOR_MAP_SWIZZLE_128B, promo, CU_TENSOR_MAP_FLOAT_OOB_FILL_NONE);
}

}

extern "C" void kernel_launch(void* const* d_in, const int* in_sizes, int n_in, void* d_out, int out_size) {
  void* fp = nullptr;
  cudaDriverEntryPointQueryResult qr;
  cudaGetDriverEntryPoint("cuTensorMapEncodeTiled", &fp, cudaEnableDefault, &qr);
  EncodeFn fn = (EncodeFn)fp;
  void *qkv = nullptr, *op = nullptr;
  cudaGetSymbolAddress(&qkv, g_qkv);
  cudaGetSymbolAddress(&op, g_o);
  Maps mp;
  encode2(fn, &mp.x, d_in[0], DM, SEQ, 64, 128, false, CU_TENSOR_MAP_L2_PROMOTION_L2_256B);
  encode2(fn, &mp.wqkv, d_in[1], 3 * DM, DM, 64, 64);
  encode2(fn, &mp.w24, d_in[1], 3 * DM, DM, 24, 64);
  encode2(fn, &mp.wg, d_in[4], FF, DM, 64, 64);
  encode2(fn, &mp.wu, d_in[5], FF, DM, 64, 64);
  encode2(fn, &mp.wd, d_in[6], DM, FF, 64, 64);
  encode2(fn, &mp.woa, d_in[2], DM, DM, 64, 64);
  encode2(fn, &mp.wob, d_in[2], DM, DM, 64, 16);
  encode2(fn, &mp.out, d_out, DM, SEQ, 64, 16);
  encode2(fn, &mp.lkv, qkv, 2 * SEQ, 216, 124, 9, true);
  encode2(fn, &mp.lq, qkv, 2 * SEQ, 216, 100, 9, true);
  encode2(fn, &mp.op, op, 18, 128 * 128, 2, 128, true);
  cudaFuncSetAttribute(fused_kernel, cudaFuncAttributeMaxDynamicSharedMemorySize, SMEM_BYTES);
  fused_kernel<<<128, 384, SMEM_BYTES, cudaStreamPerThread>>>(mp, d_in[1], 0u);
}
```

```cpp
#include <cuda_runtime.h>
#include <cuda.h>
#include <stdint.h>

namespace {

constexpr int SEQ = 2048, DM = 576, FF = 4608;
constexpr int NSLOT = 9;
constexpr int SLOT = 8192;
constexpr int HS = 16384;
constexpr int RING = NSLOT * SLOT;
constexpr int OFF_WOR = 9 * HS;
constexpr int OFF_BAR = OFF_WOR + 4 * 2048;
constexpr int SMEM_BYTES = RING + OFF_BAR + 512;
constexpr int OFF_W24 = 0;
constexpr int OTILE = 128 * 144;
constexpr int OFF_OP = OTILE, OFF_WO0 = OTILE + 2048;
constexpr int OFF_AK = 6 * HS, OFF_AQ = OFF_AK + 8960, OFF_AV = 7 * HS;
constexpr int BAR_FULL = 0, BAR_EMPTY = 9, BAR_X = 18, BAR_WOR = 27, BAR_XDONE = 28, BAR_W24 = 29, BAR_QST = 30, BAR_WOF = 31, BAR_WOE = 33,
              BAR_ATI = 35, BAR_ATD = 37, BAR_O = 39, BAR_OFREE = 40;
constexpr int SPIN_LIMIT = 1 << 20;

__device__ uint4 g_qkv[216 * SEQ];
__device__ uint32_t g_o[128 * 128 * 36];
__device__ unsigned g_cnt[16 * 32];
__device__ unsigned g_done;
__device__ unsigned g_epoch;

__device__ __forceinline__ uint32_t smem_u32(const void* p) { return (uint32_t)__cvta_generic_to_shared(p); }
__device__ __forceinline__ void wg_fence() { asm volatile("wgmma.fence.sync.aligned;\n" ::: "memory"); }
__device__ __forceinline__ void wg_commit() { asm volatile("wgmma.commit_group.sync.aligned;\n" ::: "memory"); }
template <int N> __device__ __forceinline__ void wg_wait() { asm volatile("wgmma.wait_group.sync.aligned %0;\n" ::"n"(N) : "memory"); }
__device__ __forceinline__ void mbar_init(uint32_t a, int c) { asm volatile("mbarrier.init.shared::cta.b64 [%0], %1;" ::"r"(a), "r"(c) : "memory"); }
__device__ __forceinline__ void mbar_expect(uint32_t a, uint32_t b) { asm volatile("mbarrier.arrive.expect_tx.shared::cta.b64 _, [%0], %1;" ::"r"(a), "r"(b) : "memory"); }
__device__ __forceinline__ void mbar_arrive(uint32_t a) { asm volatile("mbarrier.arrive.shared::cta.b64 _, [%0];" ::"r"(a) : "memory"); }
__device__ __forceinline__ uint32_t mbar_try(uint32_t a, uint32_t par) {
  uint32_t ok;
  asm volatile("{\n.reg .pred p;\nmbarrier.try_wait.parity.shared::cta.b64 p, [%1], %2;\nselp.u32 %0,1,0,p;\n}\n" : "=r"(ok) : "r"(a), "r"(par) : "memory");
  return ok;
}
__device__ __forceinline__ void mbar_wait(uint32_t a, uint32_t par) {
  int it = 0;
  while (true) {
    if (mbar_try(a, par)) break;
    if (++it > SPIN_LIMIT) __trap();
  }
}
__device__ __forceinline__ void fence_mbar_init() { asm volatile("fence.mbarrier_init.release.cluster;" ::: "memory"); }
__device__ __forceinline__ void fence_async_smem() { asm volatile("fence.proxy.async.shared::cta;\n" ::: "memory"); }
__device__ __forceinline__ void fence_async_gmem() { asm volatile("fence.proxy.async.global;\n" ::: "memory"); }
__device__ __forceinline__ void tma2d(uint32_t dst, const CUtensorMap* m, int c0, int c1, uint32_t bar) {
  asm volatile("cp.async.bulk.tensor.2d.shared::cluster.global.mbarrier::complete_tx::bytes [%0], [%1, {%3, %4}], [%2];" ::"r"(dst), "l"(m), "r"(bar), "r"(c0), "r"(c1) : "memory");
}
__device__ __forceinline__ void bulk_g2s(uint32_t dst, const void* src, uint32_t bytes, uint32_t bar) {
  asm volatile("cp.async.bulk.shared::cluster.global.mbarrier::complete_tx::bytes [%0], [%1], %2, [%3];" ::"r"(dst), "l"(src), "r"(bytes), "r"(bar) : "memory");
}
__device__ __forceinline__ void tma2d_store(const CUtensorMap* m, uint32_t src, int c0, int c1) {
  asm volatile("cp.async.bulk.tensor.2d.global.shared::cta.tile.bulk_group [%0, {%2, %3}], [%1];" ::"l"(m), "r"(src), "r"(c0), "r"(c1) : "memory");
}
__device__ __forceinline__ bool elect() {
  uint32_t p;
  asm volatile("{\n.reg .pred p;\nelect.sync _|p, 0xffffffff;\nselp.u32 %0, 1, 0, p;\n}\n" : "=r"(p));
  return p;
}
__device__ __forceinline__ void tma2d_red(const CUtensorMap* m, uint32_t src, int c0, int c1) {
  asm volatile("cp.reduce.async.bulk.tensor.2d.global.shared::cta.add.tile.bulk_group [%0, {%2, %3}], [%1];" ::"l"(m), "r"(src), "r"(c0), "r"(c1) : "memory");
}
__device__ __forceinline__ void bulk_commit() { asm volatile("cp.async.bulk.commit_group;" ::: "memory"); }
__device__ __forceinline__ void bulk_wait_all() { asm volatile("cp.async.bulk.wait_group 0;" ::: "memory"); }
__device__ __forceinline__ void bulk_wait_read_all() { asm volatile("cp.async.bulk.wait_group.read 0;" ::: "memory"); }
__device__ __forceinline__ void ldsm4(uint32_t addr, uint32_t& r0, uint32_t& r1, uint32_t& r2, uint32_t& r3) {
  asm volatile("ldmatrix.sync.aligned.m8n8.x4.shared.b16 {%0,%1,%2,%3}, [%4];" : "=r"(r0), "=r"(r1), "=r"(r2), "=r"(r3) : "r"(addr) : "memory");
}
__device__ __forceinline__ void ldsm4_tied(uint32_t zero, uint32_t addr, uint32_t& r0, uint32_t& r1, uint32_t& r2, uint32_t& r3) {
  asm volatile("{\n.reg .pred p;\nsetp.eq.u32 p, %5, 0;\n@p ldmatrix.sync.aligned.m8n8.x4.shared.b16 {%0,%1,%2,%3}, [%4];\n}\n"
               : "+r"(r0), "+r"(r1), "+r"(r2), "+r"(r3) : "r"(addr), "r"(zero) : "memory");
}
__device__ __forceinline__ void stsm4(uint32_t addr, uint32_t r0, uint32_t r1, uint32_t r2, uint32_t r3) {
  asm volatile("stmatrix.sync.aligned.m8n8.x4.shared.b16 [%0], {%1,%2,%3,%4};" ::"r"(addr), "r"(r0), "r"(r1), "r"(r2), "r"(r3) : "memory");
}
template <int N> __device__ __forceinline__ void lds(uint32_t addr, uint32_t* v) {
  if (N == 4) asm volatile("ld.shared.v4.b32 {%0,%1,%2,%3}, [%4];" : "=r"(v[0]), "=r"(v[1]), "=r"(v[2]), "=r"(v[3]) : "r"(addr));
  else if (N == 2) asm volatile("ld.shared.v2.b32 {%0,%1}, [%2];" : "=r"(v[0]), "=r"(v[1]) : "r"(addr));
  else asm volatile("ld.shared.b32 %0, [%1];" : "=r"(v[0]) : "r"(addr));
}
__device__ __forceinline__ uint32_t pack2(float lo, float hi) { uint32_t r; asm("cvt.rn.bf16x2.f32 %0, %1, %2;" : "=r"(r) : "f"(hi), "f"(lo)); return r; }
__device__ __forceinline__ float bf_lo(uint32_t v) { return __uint_as_float(v << 16); }
__device__ __forceinline__ float bf_hi(uint32_t v) { return __uint_as_float(v & 0xffff0000u); }
__device__ __forceinline__ uint32_t bsub2(uint32_t a, uint32_t b) { uint32_t r; asm("sub.rn.bf16x2 %0, %1, %2;" : "=r"(r) : "r"(a), "r"(b)); return r; }
__device__ __forceinline__ uint32_t bmul2(uint32_t a, uint32_t b) { uint32_t r; asm("mul.rn.bf16x2 %0, %1, %2;" : "=r"(r) : "r"(a), "r"(b)); return r; }
__device__ __forceinline__ float tanh_hw(float x) { float y; asm("tanh.approx.f32 %0, %1;" : "=f"(y) : "f"(x)); return y; }
__device__ __forceinline__ float ex2(float x) { float y; asm("ex2.approx.ftz.f32 %0, %1;" : "=f"(y) : "f"(x)); return y; }
__device__ __forceinline__ unsigned ld_acquire(const unsigned* p) { unsigned v; asm volatile("ld.acquire.gpu.global.u32 %0, [%1];" : "=r"(v) : "l"(p) : "memory"); return v; }
__device__ __forceinline__ void red_release(unsigned* p, unsigned v) { asm volatile("red.release.gpu.global.add.u32 [%0], %1;" ::"l"(p), "r"(v) : "memory"); }
__device__ __forceinline__ void wait_counter(const unsigned* p, unsigned target) {
  int it = 0;
  while ((int)(ld_acquire(p) - target) < 0) { __nanosleep(128); if (++it > SPIN_LIMIT) __trap(); }
}
__device__ __forceinline__ void mma16816(float (&d)[4], uint32_t a0, uint32_t a1, uint32_t a2, uint32_t a3, uint32_t b0, uint32_t b1) {
  asm volatile("mma.sync.aligned.m16n8k16.row.col.f32.bf16.bf16.f32 {%0,%1,%2,%3}, {%4,%5,%6,%7}, {%8,%9}, {%0,%1,%2,%3};"
               : "+f"(d[0]), "+f"(d[1]), "+f"(d[2]), "+f"(d[3]) : "r"(a0), "r"(a1), "r"(a2), "r"(a3), "r"(b0), "r"(b1));
}
__device__ __forceinline__ void mma1688(float (&d)[4], uint32_t a0, uint32_t a1, uint32_t b0) {
  asm volatile("mma.sync.aligned.m16n8k8.row.col.f32.bf16.bf16.f32 {%0,%1,%2,%3}, {%4,%5}, {%6}, {%0,%1,%2,%3};"
               : "+f"(d[0]), "+f"(d[1]), "+f"(d[2]), "+f"(d[3]) : "r"(a0), "r"(a1), "r"(b0));
}

template <int NA> __device__ __forceinline__ void wgmma_rs_n64(float (&d)[NA], uint32_t a0, uint32_t a1, uint32_t a2, uint32_t a3, uint64_t db, int sd) {
  asm volatile("{\n.reg .pred p;\nsetp.ne.b32 p, %37, 0;\n"
    "wgmma.mma_async.sync.aligned.m64n64k16.f32.bf16.bf16 {%0, %1, %2, %3, %4, %5, %6, %7, %8, %9, %10, %11, %12, %13, %14, %15, %16, %17, %18, %19, %20, %21, %22, %23, %24, %25, %26, %27, %28, %29, %30, %31}, {%32, %33, %34, %35}, %36, p, 1, 1, 1;\n"
    "}\n"
    : "+f"(d[0]), "+f"(d[1]), "+f"(d[2]), "+f"(d[3]), "+f"(d[4]), "+f"(d[5]), "+f"(d[6]), "+f"(d[7]), "+f"(d[8]), "+f"(d[9]), "+f"(d[10]), "+f"(d[11]), "+f"(d[12]), "+f"(d[13]), "+f"(d[14]), "+f"(d[15]), "+f"(d[16]), "+f"(d[17]), "+f"(d[18]), "+f"(d[19]), "+f"(d[20]), "+f"(d[21]), "+f"(d[22]), "+f"(d[23]), "+f"(d[24]), "+f"(d[25]), "+f"(d[26]), "+f"(d[27]), "+f"(d[28]), "+f"(d[29]), "+f"(d[30]), "+f"(d[31])
    : "r"(a0), "r"(a1), "r"(a2), "r"(a3), "l"(db), "r"(sd));
}

template <int NA> __device__ __forceinline__ void wgmma_ss_n64(float (&d)[NA], uint64_t da, uint64_t db, int sd) {
  asm volatile("{\n.reg .pred p;\nsetp.ne.b32 p, %34, 0;\n"
    "wgmma.mma_async.sync.aligned.m64n64k16.f32.bf16.bf16 {%0, %1, %2, %3, %4, %5, %6, %7, %8, %9, %10, %11, %12, %13, %14, %15, %16, %17, %18, %19, %20, %21, %22, %23, %24, %25, %26, %27, %28, %29, %30, %31}, %32, %33, p, 1, 1, 0, 1;\n"
    "}\n"
    : "+f"(d[0]), "+f"(d[1]), "+f"(d[2]), "+f"(d[3]), "+f"(d[4]), "+f"(d[5]), "+f"(d[6]), "+f"(d[7]), "+f"(d[8]), "+f"(d[9]), "+f"(d[10]), "+f"(d[11]), "+f"(d[12]), "+f"(d[13]), "+f"(d[14]), "+f"(d[15]), "+f"(d[16]), "+f"(d[17]), "+f"(d[18]), "+f"(d[19]), "+f"(d[20]), "+f"(d[21]), "+f"(d[22]), "+f"(d[23]), "+f"(d[24]), "+f"(d[25]), "+f"(d[26]), "+f"(d[27]), "+f"(d[28]), "+f"(d[29]), "+f"(d[30]), "+f"(d[31])
    : "l"(da), "l"(db), "r"(sd));
}

template <int NA> __device__ __forceinline__ void wgmma_rs_n88(float (&d)[NA], uint32_t a0, uint32_t a1, uint32_t a2, uint32_t a3, uint64_t db, int sd) {
  asm volatile("{\n.reg .pred p;\nsetp.ne.b32 p, %49, 0;\n"
    "wgmma.mma_async.sync.aligned.m64n88k16.f32.bf16.bf16 {%0, %1, %2, %3, %4, %5, %6, %7, %8, %9, %10, %11, %12, %13, %14, %15, %16, %17, %18, %19, %20, %21, %22, %23, %24, %25, %26, %27, %28, %29, %30, %31, %32, %33, %34, %35, %36, %37, %38, %39, %40, %41, %42, %43}, {%44, %45, %46, %47}, %48, p, 1, 1, 1;\n"
    "}\n"
    : "+f"(d[0]), "+f"(d[1]), "+f"(d[2]), "+f"(d[3]), "+f"(d[4]), "+f"(d[5]), "+f"(d[6]), "+f"(d[7]), "+f"(d[8]), "+f"(d[9]), "+f"(d[10]), "+f"(d[11]), "+f"(d[12]), "+f"(d[13]), "+f"(d[14]), "+f"(d[15]), "+f"(d[16]), "+f"(d[17]), "+f"(d[18]), "+f"(d[19]), "+f"(d[20]), "+f"(d[21]), "+f"(d[22]), "+f"(d[23]), "+f"(d[24]), "+f"(d[25]), "+f"(d[26]), "+f"(d[27]), "+f"(d[28]), "+f"(d[29]), "+f"(d[30]), "+f"(d[31]), "+f"(d[32]), "+f"(d[33]), "+f"(d[34]), "+f"(d[35]), "+f"(d[36]), "+f"(d[37]), "+f"(d[38]), "+f"(d[39]), "+f"(d[40]), "+f"(d[41]), "+f"(d[42]), "+f"(d[43])
    : "r"(a0), "r"(a1), "r"(a2), "r"(a3), "l"(db), "r"(sd));
}

template <int NA> __device__ __forceinline__ void wgmma_ss_n88(float (&d)[NA], uint64_t da, uint64_t db, int sd) {
  asm volatile("{\n.reg .pred p;\nsetp.ne.b32 p, %46, 0;\n"
    "wgmma.mma_async.sync.aligned.m64n88k16.f32.bf16.bf16 {%0, %1, %2, %3, %4, %5, %6, %7, %8, %9, %10, %11, %12, %13, %14, %15, %16, %17, %18, %19, %20, %21, %22, %23, %24, %25, %26, %27, %28, %29, %30, %31, %32, %33, %34, %35, %36, %37, %38, %39, %40, %41, %42, %43}, %44, %45, p, 1, 1, 0, 1;\n"
    "}\n"
    : "+f"(d[0]), "+f"(d[1]), "+f"(d[2]), "+f"(d[3]), "+f"(d[4]), "+f"(d[5]), "+f"(d[6]), "+f"(d[7]), "+f"(d[8]), "+f"(d[9]), "+f"(d[10]), "+f"(d[11]), "+f"(d[12]), "+f"(d[13]), "+f"(d[14]), "+f"(d[15]), "+f"(d[16]), "+f"(d[17]), "+f"(d[18]), "+f"(d[19]), "+f"(d[20]), "+f"(d[21]), "+f"(d[22]), "+f"(d[23]), "+f"(d[24]), "+f"(d[25]), "+f"(d[26]), "+f"(d[27]), "+f"(d[28]), "+f"(d[29]), "+f"(d[30]), "+f"(d[31]), "+f"(d[32]), "+f"(d[33]), "+f"(d[34]), "+f"(d[35]), "+f"(d[36]), "+f"(d[37]), "+f"(d[38]), "+f"(d[39]), "+f"(d[40]), "+f"(d[41]), "+f"(d[42]), "+f"(d[43])
    : "l"(da), "l"(db), "r"(sd));
}


__device__ __forceinline__ uint64_t mkd(uint32_t lo) { return ((uint64_t)0x40000040u << 32) | (uint64_t)lo; }

constexpr uint32_t sr = 1024, sb = sr + RING;
constexpr uint32_t bars = sb + OFF_BAR;
constexpr uint32_t RING_LO = (sr >> 4) | (512u << 16);

template <int NA> __device__ __forceinline__ void acc_fence(float (&d)[NA]) {
  asm volatile("" : "+f"(d[0]), "+f"(d[1]), "+f"(d[2]), "+f"(d[3]), "+f"(d[4]), "+f"(d[5]), "+f"(d[6]), "+f"(d[7]), "+f"(d[8]), "+f"(d[9]), "+f"(d[10]), "+f"(d[11]), "+f"(d[12]), "+f"(d[13]), "+f"(d[14]), "+f"(d[15]), "+f"(d[16]), "+f"(d[17]), "+f"(d[18]), "+f"(d[19]), "+f"(d[20]), "+f"(d[21]), "+f"(d[22]), "+f"(d[23]), "+f"(d[24]), "+f"(d[25]), "+f"(d[26]), "+f"(d[27]), "+f"(d[28]), "+f"(d[29]), "+f"(d[30]), "+f"(d[31]) :: "memory");
}

template <int V> struct IC { static constexpr int value = V; };

template <int PH, bool FIRST, int NA, class M, class F>
__device__ __forceinline__ void run_pass(float (&other)[NA], M&& mma, F&& slice) {
#pragma unroll
  for (int s = 0; s < 9; s++) {
    wg_fence();
    mma(s, RING_LO + s * (SLOT >> 4));
    wg_commit();
    mbar_wait(bars + (BAR_FULL + (s + 1) % 9) * 8, s < 8 ? PH : PH ^ 1);
    slice(s);
    wg_wait<1>();
    if (s == 0) acc_fence(other);
    if ((s || !FIRST) && (threadIdx.x & 127) == 0) mbar_arrive(bars + (BAR_EMPTY + (s + 8) % 9) * 8);
  }
}

template <int BUF, int PH, bool FIRST, int NA, class M, class F>
__device__ __forceinline__ void run_down(uint32_t wpar, bool last, float (&other)[NA], M&& mma, F&& slice) {
#pragma unroll
  for (int s = 0; s < 10; s++) {
    wg_fence();
    mma(s, s < 9 ? RING_LO + s * (SLOT >> 4) : ((sb + 8 * HS + BUF * SLOT) >> 4) | (512u << 16));
    wg_commit();
    if (s < 8) mbar_wait(bars + (BAR_FULL + s + 1) * 8, PH);
    else if (s == 8) mbar_wait(bars + (BAR_WOF + BUF) * 8, wpar);
    else if (!last) mbar_wait(bars + BAR_FULL * 8, PH ^ 1);
    slice(s);
    wg_wait<1>();
    if (s == 0) acc_fence(other);
    if ((threadIdx.x & 127) == 0) {
      if (s) mbar_arrive(bars + (BAR_EMPTY + s - 1) * 8);
      else {
        if (FIRST) { mbar_arrive(bars + (BAR_EMPTY + 8) * 8); mbar_arrive(bars + (BAR_WOE + BUF) * 8); }
        mbar_arrive(bars + (BAR_WOE + (BUF ^ 1)) * 8);
      }
    }
  }
}

struct Maps {
  CUtensorMap x, wqkv, w24, wg, wu, wd, woa, wob, out, lkv, lq, op;
};

__global__ void __launch_bounds__(384, 1)
fused_kernel(const __grid_constant__ Maps mp, uint32_t zero) {
  extern __shared__ __align__(1024) uint8_t smem[];
  const int j = (blockIdx.x >> 2) & 7, m = (blockIdx.x & 3) + ((blockIdx.x >> 3) & 12);
  const int m0 = m * 128;
  if (threadIdx.x == 256) {
#pragma unroll
    for (int i = 0; i < 9; i++) {
      const uint32_t b = bars + (BAR_X + i) * 8;
      mbar_init(b, 1);
      fence_mbar_init();
      mbar_expect(b, HS);
      tma2d(sb + i * HS, &mp.x, i * 64, m0, b);
    }
  }
  const int warp = __shfl_sync(0xffffffffu, threadIdx.x >> 5, 0), lane = threadIdx.x & 31;

  asm volatile("" ::: "memory");
  if (lane == 0) {
    if (warp == 9) {
      if (smem_u32(smem) != sr) __trap();
      for (int i = 0; i < NSLOT; i++) { mbar_init(bars + (BAR_FULL + i) * 8, 1); mbar_init(bars + (BAR_EMPTY + i) * 8, 2); }
      fence_mbar_init();
    } else if (warp == 10) {
      mbar_init(bars + BAR_WOR * 8, 1);
      mbar_init(bars + BAR_XDONE * 8, 9);
      mbar_init(bars + BAR_W24 * 8, 1);
      mbar_init(bars + BAR_QST * 8, 8);
      for (int i = 0; i < 2; i++) { mbar_init(bars + (BAR_WOF + i) * 8, 1); mbar_init(bars + (BAR_WOE + i) * 8, 2); }
      for (int i = 0; i < 2; i++) { mbar_init(bars + (BAR_ATI + i) * 8, 1); mbar_init(bars + (BAR_ATD + i) * 8, 1); }
      mbar_init(bars + BAR_O * 8, 1);
      mbar_init(bars + BAR_OFREE * 8, 8);
      fence_mbar_init();
    }
  }
  __syncthreads();

  if (warp < 8) {
    asm volatile("setmaxnreg.inc.sync.aligned.u32 232;\n");
    const int wg = warp >> 2;
    const int lrow = (warp & 3) * 16 + (lane & 15);
    const uint32_t rowa = sb + wg * 8192 + lrow * 128;
    const uint32_t swz = ((lane >> 4) ^ (lrow & 7)) << 4;
    uint32_t adr[4];
#pragma unroll
    for (int i = 0; i < 4; i++) { adr[i] = rowa + (swz ^ (i << 5)); asm volatile("" : "+r"(adr[i])); }
    uint32_t a[128];
    uint32_t sg[16], oq[4], oz[4];
    float accA[32], accB[44];
    float rs0, rs1, rh0, rh1;
    uint32_t mp0, mp1;
    {
      float cs[2][4] = {}, c1[2][4] = {}, c2[2][4] = {};
      mbar_wait(bars + BAR_X * 8, 0);
#pragma unroll
      for (int kb = 0; kb < 9; kb++) {
        uint32_t ok = 1;
        if (kb < 8) ok = mbar_try(bars + (BAR_X + kb + 1) * 8, 0);
        uint32_t* r = (kb < 8) ? &a[kb * 16] : sg;
#pragma unroll
        for (int kk = 0; kk < 4; kk++) ldsm4(adr[kk] + kb * HS, r[kk * 4], r[kk * 4 + 1], r[kk * 4 + 2], r[kk * 4 + 3]);
#pragma unroll
        for (int kk = 0; kk < 4; kk++, r += 4) {
          mma16816(cs[kk & 1], r[0], r[1], r[2], r[3], 0x3f803f80u, 0x3f803f80u);
          mma1688(c1[0], r[0], r[1], r[0]);
          mma1688(c2[0], r[0], r[1], r[1]);
          mma1688(c1[1], r[2], r[3], r[2]);
          mma1688(c2[1], r[2], r[3], r[3]);
        }
        if (!ok) mbar_wait(bars + (BAR_X + kb + 1) * 8, 0);
      }
      __syncwarp();
      if (lane == 0) mbar_arrive(bars + BAR_XDONE * 8);
      const float mu0 = (cs[0][0] + cs[1][0]) * (1.f / DM), mu1 = (cs[0][2] + cs[1][2]) * (1.f / DM);
      mp0 = pack2(mu0, mu0); mp1 = pack2(mu1, mu1);
      rs0 = (lane & 4) ? c1[0][1] + c1[1][1] : c1[0][0] + c1[1][0];
      rs1 = (lane & 4) ? c2[0][3] + c2[1][3] : c2[0][2] + c2[1][2];
      rh0 = mu0 * mu0; rh1 = mu1 * mu1;
    }
    auto finish_rstd = [&]() {
      const int src = (lane & ~3) | (lane >> 3);
      rs0 = rsqrtf(fmaxf(__shfl_sync(0xffffffffu, rs0, src) * (1.f / DM) - rh0, 0.f) + 1e-5f);
      rs1 = rsqrtf(fmaxf(__shfl_sync(0xffffffffu, rs1, src) * (1.f / DM) - rh1, 0.f) + 1e-5f);
      rh0 = 0.5f * rs0; rh1 = 0.5f * rs1;
    };
    auto centre = [&](int kb) {
#pragma unroll
      for (int i = kb * 16; i < kb * 16 + 16; i++) a[i] = bsub2(a[i], (i & 1) ? mp1 : mp0);
    };
    centre(0);

    const uint32_t xlo = ((sb + 8 * HS + wg * 8192) >> 4) | (1u << 16);

    auto rs64 = [&](auto& acc, int kb, uint32_t blo, bool first) {
#pragma unroll
      for (int kk = 0; kk < 4; kk++)
        wgmma_rs_n64(acc, a[kb * 16 + kk * 4], a[kb * 16 + kk * 4 + 1], a[kb * 16 + kk * 4 + 2], a[kb * 16 + kk * 4 + 3], mkd(blo + kk * 128), !(first && kk == 0));
    };
    auto ss64 = [&](auto& acc, int slot, uint32_t blo) {
#pragma unroll
      for (int kk = 0; kk < 4; kk++) wgmma_ss_n64(acc, mkd(xlo - (8 - slot) * (HS >> 4) + kk * 2), mkd(blo + kk * 128), 1);
    };
    auto mma64 = [&](auto& acc, int s, uint32_t blo) { if (s < 8) rs64(acc, s, blo, s == 0); else ss64(acc, 8, blo); };
    char* qp = reinterpret_cast<char*>(g_qkv + (j * 24) * SEQ + m0 + (threadIdx.x >> 5) * 16) + (threadIdx.x & 31) * 4;
    auto qkv_store = [&](const auto& acc, int nb, int chunk) {
      *reinterpret_cast<uint32_t*>(qp + chunk * (SEQ * 16)) = pack2(acc[4 * nb] * rs0, acc[4 * nb + 1] * rs0);
      *reinterpret_cast<uint32_t*>(qp + chunk * (SEQ * 16) + 128) = pack2(acc[4 * nb + 2] * rs1, acc[4 * nb + 3] * rs1);
    };
    auto sig_slice = [&](const auto& acc, int s) {
      if (s >= 1) {
#pragma unroll
        for (int e = 2 * (s - 1); e < 2 * s; e++) {
          const float r = (e & 1) ? rh1 : rh0;
          sg[e] = pack2(fmaf(tanh_hw(acc[2 * e] * r), r, r), fmaf(tanh_hw(acc[2 * e + 1] * r), r, r));
        }
      }
    };
    auto h_val = [&](const auto& acc, int e) { return bmul2(sg[e], pack2(acc[2 * e], acc[2 * e + 1])); };
    auto load_h = [&](int pos) {
#pragma unroll
      for (int kk = (pos & 1) * 2; kk < (pos & 1) * 2 + 2; kk++) {
        const int kb = pos >> 1;
        ldsm4_tied(zero, adr[kk] + kb * HS, a[kb * 16 + kk * 4], a[kb * 16 + kk * 4 + 1], a[kb * 16 + kk * 4 + 2], a[kb * 16 + kk * 4 + 3]);
      }
    };

    mbar_wait(bars + BAR_FULL * 8, 0);
    run_pass<0, true>(accA, [&](int s, uint32_t b) { mma64(accB, s, b); }, [&](int s) {
      if (s < 7) centre(s + 1);
      if (s == 0) finish_rstd();
      if (s == 6) {
        mbar_wait(bars + BAR_XDONE * 8, 0);
#pragma unroll
        for (int i = 0; i < 16; i++) sg[i] = bsub2(sg[i], (i & 1) ? mp1 : mp0);
#pragma unroll
        for (int kk = 0; kk < 4; kk++) stsm4(adr[kk] + 8 * HS, sg[kk * 4], sg[kk * 4 + 1], sg[kk * 4 + 2], sg[kk * 4 + 3]);
        fence_async_smem();
      }
      if (s == 7) asm volatile("bar.sync %0, 128;" ::"r"(1 + wg) : "memory");
    });
    run_pass<1, false>(accB, [&](int s, uint32_t b) { mma64(accA, s, b); }, [&](int s) {
      if (s >= 1) qkv_store(accB, s - 1, s - 1);
      if (s == 8) mbar_wait(bars + BAR_W24 * 8, 0);
    });
    run_pass<0, false>(accA, [&](int s, uint32_t b) {
      const uint32_t lo = (b & 0xffffu) | (((OFF_W24 + RING) >> 4) << 16);
#pragma unroll
      for (int kk = 0; kk < 4; kk++) {
        const int k = s * 4 + kk;
        if (s < 8) wgmma_rs_n88(accB, a[k * 4], a[k * 4 + 1], a[k * 4 + 2], a[k * 4 + 3], mkd(lo + kk * 128), k != 0);
        else wgmma_ss_n88(accB, mkd(xlo + kk * 2), mkd(lo + kk * 128), 1);
      }
    }, [&](int s) { if (s >= 1) qkv_store(accA, s - 1, 7 + s); });
    run_pass<1, false>(accB, [&](int s, uint32_t b) { mma64(accA, s, b); }, [&](int s) {
      if (s == 1) asm volatile("" : "+f"(accB[32]), "+f"(accB[33]), "+f"(accB[34]), "+f"(accB[35]), "+f"(accB[36]), "+f"(accB[37]), "+f"(accB[38]),
                               "+f"(accB[39]), "+f"(accB[40]), "+f"(accB[41]), "+f"(accB[42]), "+f"(accB[43]) :: "memory");
      if (s >= 1 && s <= 4) { qkv_store(accB, 2 * s - 2, 14 + 2 * s); qkv_store(accB, 2 * s - 1, 15 + 2 * s); }
      if (s == 5) { qp += (192 - 21 * j) * (SEQ * 16); qkv_store(accB, 8, 0); qkv_store(accB, 9, 1); }
      if (s == 6) {
        qkv_store(accB, 10, 2);
        __syncwarp();
        if (lane == 0) mbar_arrive(bars + BAR_QST * 8);
      }
    });
    for (int c = 0; c < 8; c++) {
      run_pass<0, false>(accA, [&](int s, uint32_t b) { mma64(accB, s, b); }, [&](int s) { sig_slice(accA, s); });
      run_pass<1, false>(accB, [&](int s, uint32_t b) { mma64(accA, s, b); }, [&](int s) {
        if (s == 1 && c >= 6) mbar_wait(bars + (BAR_ATD - 6 + c) * 8, 0);
        if (s >= 1 && s <= 7 && (s & 1)) {
          const int t = s >> 1;
          stsm4(adr[t] + c * HS, h_val(accB, 4 * t), h_val(accB, 4 * t + 1), h_val(accB, 4 * t + 2), h_val(accB, 4 * t + 3));
        }
      });
    }
    run_pass<0, false>(accA, [&](int s, uint32_t b) { mma64(accB, s, b); }, [&](int s) {
      sig_slice(accA, s);
      if (s == 0) {
        fence_async_smem();
        asm volatile("bar.sync %0, 128;" ::"r"(1 + wg) : "memory");
      }
      if (s >= 2) load_h(s - 2);
      if (s == 6) {
        __syncwarp();
        if (lane == 0) mbar_arrive(bars + BAR_OFREE * 8);
      }
    });
    constexpr uint32_t worlo = ((sb + OFF_WOR) >> 4) | (512u << 16);
    const int grow = m0 + warp * 16;
    int blk = j;
    auto mmaD = [&](auto& acc, int s, uint32_t blo, const uint32_t* sh, uint32_t shlo) {
      if (s < 6) rs64(acc, s, blo, s == 0);
      else if (s < 8) ss64(acc, s, blo);
      else rs64(acc, s - 2, blo, false);
      if (s == 9 && sh) wgmma_rs_n64(acc, sh[0], sh[1], sh[2], sh[3], mkd(shlo), 1);
    };
    auto flush_store = [&](const auto& acc, int slot, int t) {
      stsm4(adr[t] + slot * HS, pack2(acc[8 * t], acc[8 * t + 1]), pack2(acc[8 * t + 2], acc[8 * t + 3]),
            pack2(acc[8 * t + 4], acc[8 * t + 5]), pack2(acc[8 * t + 6], acc[8 * t + 7]));
    };
    auto flush_issue = [&](int slot, int cb) {
      fence_async_smem();
      __syncwarp();
      if (elect()) { tma2d_red(&mp.out, sb + slot * HS + warp * 2048, cb * 64, grow); bulk_commit(); }
    };
    run_down<0, 1, true>(0, false, accB, [&](int s, uint32_t b) { mmaD(accA, s, b, oz, ((sb + OFF_WO0) >> 4) | (512u << 16)); }, [&](int s) {
      if (s < 5) load_h(7 + s);
      if (s >= 1 && s <= 4) {
#pragma unroll
        for (int e = 4 * (s - 1); e < 4 * s; e++) a[96 + e] = h_val(accB, e);
      }
      if (s == 7) {
        mbar_wait(bars + BAR_WOR * 8, 0);
        mbar_wait(bars + BAR_O * 8, 0);
        fence_async_gmem();
        const uint32_t orow = (threadIdx.x >> 5) * 16 + (threadIdx.x & 15), oa = sb + orow * 144, odd = j & 1;
#pragma unroll
        for (int kk = 0; kk < 4; kk++) ldsm4(oa + odd * 16 + kk * 32 + (threadIdx.x & 16), a[112 + kk * 4], a[113 + kk * 4], a[114 + kk * 4], a[115 + kk * 4]);
        ldsm4(((threadIdx.x >> 4) & 1) == odd ? oa + 128 - odd * 128 : sb + OFF_OP + orow * 16, oq[0], oq[1], oq[2], oq[3]);
#pragma unroll
        for (int i = 0; i < 4; i++) asm volatile("mul.lo.u32 %0, %1, %2;" : "=r"(oz[i]) : "r"(oq[i]), "r"(odd ^ 1));
      }
    });
    auto flush_slice = [&](const auto& acc, int slot, int cb, int s) {
      if (s == 0) { asm volatile("cp.async.bulk.wait_group.read 1;" ::: "memory"); __syncwarp(); }
      if (s >= 1 && s <= 4) flush_store(acc, slot, s - 1);
      if (s == 5) flush_issue(slot, cb);
    };
    for (int p = 1; p < 9; p += 2) {
      int pb = blk; blk = (blk == 8) ? 0 : blk + 1;
      run_down<1, 0, false>((p >> 1) & 1, false, accA, [&](int s, uint32_t b) { mmaD(accB, s, b, oq, worlo + (p >> 1) * 128); }, [&](int s) { flush_slice(accA, 2, pb, s); });
      pb = blk; blk = (blk == 8) ? 0 : blk + 1;
      if (p == 7 && wg == 1) asm volatile("bar.sync 5, 256;" ::: "memory");
      run_down<0, 1, false>(((p + 1) >> 1) & 1, p == 7, accB, [&](int s, uint32_t b) { mmaD(accA, s, b, nullptr, 0); }, [&](int s) {
        flush_slice(accB, 3, pb, s);
        if (s == 3 && p == 7 && wg == 0) asm volatile("bar.arrive 5, 256;" ::: "memory");
      });
    }
    flush_slice(accA, 2, blk, 0);
    wg_wait<0>();
    acc_fence(accA);
#pragma unroll
    for (int t = 1; t <= 5; t++) flush_slice(accA, 2, blk, t);
    bulk_wait_read_all();
  } else {
    asm volatile("setmaxnreg.dec.sync.aligned.u32 40;\n");
    if (warp == 8) {
      int st = 0; uint32_t ph = 1;
      auto stage = [&](const CUtensorMap* w, int c0, int c1) {
        mbar_wait(bars + (BAR_EMPTY + st) * 8, ph);
        const uint32_t fb = bars + (BAR_FULL + st) * 8;
        if (elect()) {
          mbar_expect(fb, SLOT);
          tma2d(sr + st * SLOT, w, c0, c1, fb);
        }
        st++;
        if (st == NSLOT) { st = 0; ph ^= 1; }
      };
      int blk = j;
#pragma unroll 1
      for (int p = 0; p < 30; p++) {
        const CUtensorMap* w; int c0, c1 = 0;
        if (p < 3) { w = &mp.wqkv; c0 = j * 192 + p * 64; }
        else if (p < 21) { w = (p & 1) ? &mp.wg : &mp.wu; c0 = j * 576 + ((p - 3) >> 1) * 64; }
        else { w = &mp.wd; c0 = blk * 64; c1 = j * 576; }
#pragma unroll 1
        for (int kb = 0; kb < 9; kb++) {
          stage(w, c0, c1 + kb * 64);
        }
        if (p >= 21) {
          const int q = p - 21;
          mbar_wait(bars + (BAR_WOE + (q & 1)) * 8, (q >> 1) & 1);
          if (elect()) {
            mbar_expect(bars + (BAR_WOF + (q & 1)) * 8, SLOT);
            tma2d(sb + 8 * HS + (q & 1) * SLOT, &mp.woa, c0, j * 72 + (j & 1) * 8, bars + (BAR_WOF + (q & 1)) * 8);
          }
          blk = (blk == 8) ? 0 : blk + 1;
        }
      }
    } else {
      const int aw = warp - 9;
      if (aw == 2 && elect()) {
        const CUtensorMap* mm = &mp.w24;
#pragma unroll 1
        for (int i = 0; i < 10; i++) asm volatile("prefetch.tensormap [%0];" ::"l"(mm + i) : "memory");
      }
      const unsigned target = (*(volatile unsigned*)&g_epoch + 1) * 8;
      if (aw == 1) {
#pragma unroll 1
        for (int kb = 0; kb < 9; kb++) {
          mbar_wait(bars + (BAR_X + kb) * 8, 0);
          if (elect()) tma2d_store(&mp.out, sb + kb * HS + j * 2048, kb * 64, m0 + j * 16);
        }
        if (elect()) bulk_commit();
        bulk_wait_read_all();
        __syncwarp();
        if (lane == 0) mbar_arrive(bars + BAR_XDONE * 8);
      }
      if (aw == 2) {
        mbar_wait(bars + BAR_XDONE * 8, 0);
        if (elect()) { mbar_expect(bars + BAR_W24 * 8, 9 * 64 * 48); mbar_expect(bars + BAR_WOR * 8, 4 * 2048); }
#pragma unroll 1
        for (int b = 0; b < 13; b++) {
          if (elect()) {
            if (b < 9) tma2d(sb + OFF_W24 + b * SLOT, &mp.w24, 1536 + j * 24, b * 64, bars + BAR_W24 * 8);
            else tma2d(sb + OFF_WOR + (b - 9) * 2048, &mp.wob, ((j + 2 * b - 17) % 9) * 64, (j & ~1) * 72 + 64, bars + BAR_WOR * 8);
          }
          __nanosleep(64);
        }
      }
      if (aw == 1) bulk_wait_all();
      asm volatile("bar.sync 3, 96;" ::: "memory");
      auto load_kq = [&](int t) {
        const int r2 = (m0 + t * 48) * 2;
        mbar_expect(bars + BAR_ATI * 8, 9 * (62 + 50) * 16);
        tma2d(sb + OFF_AK, &mp.lkv, r2 - 28, 72 + j * 9, bars + BAR_ATI * 8);
        tma2d(sb + OFF_AQ, &mp.lq, r2, j * 9, bars + BAR_ATI * 8);
      };
      auto load_v = [&](int t) {
        mbar_expect(bars + (BAR_ATI + 1) * 8, 9 * 62 * 16);
        tma2d(sb + OFF_AV, &mp.lkv, (m0 + t * 48) * 2 - 28, 144 + j * 9, bars + (BAR_ATI + 1) * 8);
      };
      if (aw == 0) {
        mbar_wait(bars + BAR_QST * 8, 0);
        if (lane == 0) red_release(&g_cnt[m * 32], 1);
        if (lane < 2) wait_counter(&g_cnt[(lane && m ? m - 1 : m) * 32], target);
        __syncwarp();
        fence_async_gmem();
        if (elect()) { load_kq(0); load_v(0); }
      }
      uint32_t l16 = (aw * 16 + (lane & 1) + (lane & 2) * 2 + (lane >> 4) * 8) * 16;
      auto fresh = [&]() { asm volatile("" : "+r"(l16)); return l16; };
      const float sc = 0.23570226039551584f * 1.4426950408889634f;
#pragma unroll 1
      for (int t = 0; t < 3; t++) {
        const bool active = t < 2 || aw < 2;
        float p0[8] = {}, p1[8] = {};
        uint32_t h8 = (threadIdx.x & 12) * 2;
        asm volatile("" : "+r"(h8));
        const uint32_t po = (0x70482800u >> h8) & 255, po3 = (0x6C682420u >> h8) & 255;
        const uint32_t px = (0x00100000u >> h8) & 255;
        mbar_wait(bars + BAR_ATI * 8, t & 1);
        if (active) {
          auto qk = [&](auto nw, uint32_t b) {
            constexpr int N = decltype(nw)::value;
            uint32_t u[N]; float q0[2 * N], q1[2 * N];
            const uint32_t o = fresh() + (b & 15), qa = o + (b >> 4) * 800 + (sb + OFF_AQ), ka = o + (b >> 4) * 992 + (sb + OFF_AK);
            lds<N>(qa, u);
#pragma unroll
            for (int i = 0; i < N; i++) { q0[2 * i] = bf_lo(u[i]); q0[2 * i + 1] = bf_hi(u[i]); }
            lds<N>(qa + 32, u);
#pragma unroll
            for (int i = 0; i < N; i++) { q1[2 * i] = bf_lo(u[i]); q1[2 * i + 1] = bf_hi(u[i]); }
#pragma unroll
            for (int s = 0; s < 9; s++) {
              lds<N>(ka + (16 - 2 * s) * 16, u);
#pragma unroll
              for (int i = 0; i < N; i++) {
                const float lo = bf_lo(u[i]), hi = bf_hi(u[i]);
                if (s < 8) { p1[s] = fmaf(q1[2 * i], lo, p1[s]); p1[s] = fmaf(q1[2 * i + 1], hi, p1[s]); }
                if (s > 0) { p0[s - 1] = fmaf(q0[2 * i], lo, p0[s - 1]); p0[s - 1] = fmaf(q0[2 * i + 1], hi, p0[s - 1]); }
              }
            }
          };
#pragma unroll 1
          for (int i = 0; i < 4; i++) qk(IC<2>(), po + ((8 * i) ^ px));
          qk(IC<1>(), po3);
        }
        asm volatile("bar.sync 3, 96;" ::: "memory");
        if (aw == 0 && elect()) { if (t < 2) load_kq(t + 1); else mbar_arrive(bars + BAR_ATD * 8); }
        if (active) {
          if (m0 + t == 0) {
            const int row = fresh() >> 4;
#pragma unroll
            for (int w = 1; w < 8; w++) { if (row < 2 * w) p0[w] = -INFINITY; if (row + 2 < 2 * w) p1[w] = -INFINITY; }
          }
          auto softmax = [&](float (&p)[8]) {
            const float mx = fmaxf(fmaxf(fmaxf(p[0], p[1]), fmaxf(p[2], p[3])), fmaxf(fmaxf(p[4], p[5]), fmaxf(p[6], p[7])));
            float l = 0.f;
#pragma unroll
            for (int w = 0; w < 8; w++) { p[w] = ex2((p[w] - mx) * sc); l += p[w]; }
            l = __fdividef(1.f, l);
#pragma unroll
            for (int w = 0; w < 8; w++) p[w] *= l;
          };
          softmax(p0); softmax(p1);
        }
        mbar_wait(bars + (BAR_ATI + 1) * 8, t & 1);
        if (active) {
          char* op = reinterpret_cast<char*>(g_o + (blockIdx.x * 128 + t * 48) * 36) + fresh() * 9;
          auto pv = [&](auto nw, uint32_t b) {
            constexpr int N = decltype(nw)::value;
            uint32_t u[N]; float o0[2 * N] = {}, o1[2 * N] = {};
            const uint32_t va = fresh() + (b & 15) + (b >> 4) * 992 + (sb + OFF_AV);
#pragma unroll
            for (int s = 0; s < 9; s++) {
              lds<N>(va + (16 - 2 * s) * 16, u);
#pragma unroll
              for (int i = 0; i < N; i++) {
                const float lo = bf_lo(u[i]), hi = bf_hi(u[i]);
                if (s < 8) { o1[2 * i] = fmaf(p1[s], lo, o1[2 * i]); o1[2 * i + 1] = fmaf(p1[s], hi, o1[2 * i + 1]); }
                if (s > 0) { o0[2 * i] = fmaf(p0[s - 1], lo, o0[2 * i]); o0[2 * i + 1] = fmaf(p0[s - 1], hi, o0[2 * i + 1]); }
              }
            }
            if (N == 2) {
              *reinterpret_cast<uint2*>(op + b) = make_uint2(pack2(o0[0], o0[1]), pack2(o0[2 % (2 * N)], o0[3 % (2 * N)]));
              *reinterpret_cast<uint2*>(op + b + 288) = make_uint2(pack2(o1[0], o1[1]), pack2(o1[2 % (2 * N)], o1[3 % (2 * N)]));
            } else {
              *reinterpret_cast<uint32_t*>(op + b) = pack2(o0[0], o0[1]);
              *reinterpret_cast<uint32_t*>(op + b + 288) = pack2(o1[0], o1[1]);
            }
          };
#pragma unroll 1
          for (int i = 0; i < 4; i++) pv(IC<2>(), po + ((8 * i) ^ px));
          pv(IC<1>(), po3);
        }
        asm volatile("bar.sync 3, 96;" ::: "memory");
        if (aw == 0 && elect()) { if (t < 2) load_v(t + 1); else mbar_arrive(bars + (BAR_ATD + 1) * 8); }
      }
      if (aw == 0) {
        if (elect()) {
          red_release(&g_cnt[m * 32 + 8 + (j >> 1)], 1);
          wait_counter(&g_cnt[m * 32 + 8 + (j >> 1)], (*(volatile unsigned*)&g_epoch + 1) * 2);
        }
        __syncwarp();
        mbar_wait(bars + BAR_OFREE * 8, 0);
        fence_async_gmem();
        if (elect()) {
          mbar_expect(bars + BAR_O * 8, OTILE + 4096);
          bulk_g2s(sb, g_o + blockIdx.x * 128 * 36, OTILE, bars + BAR_O * 8);
          tma2d(sb + OFF_OP, &mp.op, (j & 1) * 16, (blockIdx.x ^ 4) * 128, bars + BAR_O * 8);
          tma2d(sb + OFF_WO0, &mp.wob, j * 64, (j & ~1) * 72 + 64, bars + BAR_O * 8);
          if (atomicInc(&g_done, 127u) == 127u) atomicAdd(&g_epoch, 1u);
        }
      }
    }
  }
}

typedef CUresult (*EncodeFn)(CUtensorMap*, CUtensorMapDataType, cuuint32_t, void*, const cuuint64_t*, const cuuint64_t*, const cuuint32_t*,
                             const cuuint32_t*, CUtensorMapInterleave, CUtensorMapSwizzle, CUtensorMapL2promotion, CUtensorMapFloatOOBfill);

void encode2(EncodeFn fn, CUtensorMap* m, const void* p, uint64_t cols, uint64_t rows, uint32_t bc, uint32_t br, bool raw = false,
             CUtensorMapL2promotion promo = CU_TENSOR_MAP_L2_PROMOTION_L2_128B) {
  const cuuint64_t d[2] = {cols, rows}, s[1] = {cols * (raw ? 8 : 2)};
  const cuuint32_t b[2] = {bc, br}, es[2] = {1, 1};
  fn(m, raw ? CU_TENSOR_MAP_DATA_TYPE_UINT64 : CU_TENSOR_MAP_DATA_TYPE_BFLOAT16, 2, const_cast<void*>(p), d, s, b, es, CU_TENSOR_MAP_INTERLEAVE_NONE,
     raw ? CU_TENSOR_MAP_SWIZZLE_NONE : CU_TENSOR_MAP_SWIZZLE_128B, promo, CU_TENSOR_MAP_FLOAT_OOB_FILL_NONE);
}

}

extern "C" void kernel_launch(void* const* d_in, const int* in_sizes, int n_in, void* d_out, int out_size) {
  void* fp = nullptr;
  cudaDriverEntryPointQueryResult qr;
  cudaGetDriverEntryPoint("cuTensorMapEncodeTiled", &fp, cudaEnableDefault, &qr);
  EncodeFn fn = (EncodeFn)fp;
  void *qkv = nullptr, *op = nullptr;
  cudaGetSymbolAddress(&qkv, g_qkv);
  cudaGetSymbolAddress(&op, g_o);
  Maps mp;
  encode2(fn, &mp.x, d_in[0], DM, SEQ, 64, 128, false, CU_TENSOR_MAP_L2_PROMOTION_L2_256B);
  encode2(fn, &mp.wqkv, d_in[1], 3 * DM, DM, 64, 64);
  encode2(fn, &mp.w24, d_in[1], 3 * DM, DM, 24, 64);
  encode2(fn, &mp.wg, d_in[4], FF, DM, 64, 64);
  encode2(fn, &mp.wu, d_in[5], FF, DM, 64, 64);
  encode2(fn, &mp.wd, d_in[6], DM, FF, 64, 64);
  encode2(fn, &mp.woa, d_in[2], DM, DM, 64, 64);
  encode2(fn, &mp.wob, d_in[2], DM, DM, 64, 16);
  encode2(fn, &mp.out, d_out, DM, SEQ, 64, 16);
  encode2(fn, &mp.lkv, qkv, 2 * SEQ, 216, 124, 9, true);
  encode2(fn, &mp.lq, qkv, 2 * SEQ, 216, 100, 9, true);
  encode2(fn, &mp.op, op, 18, 128 * 128, 2, 128, true);
  cudaFuncSetAttribute(fused_kernel, cudaFuncAttributeMaxDynamicSharedMemorySize, SMEM_BYTES);
  fused_kernel<<<128, 384, SMEM_BYTES, cudaStreamPerThread>>>(mp, 0u);
}
```

```cpp
#include <cuda_runtime.h>
#include <cuda.h>
#include <stdint.h>

namespace {

constexpr int SEQ = 2048, DM = 576, FF = 4608;
constexpr int NSLOT = 9;
constexpr int SLOT = 8192;
constexpr int HS = 16384;
constexpr int RING = NSLOT * SLOT;
constexpr int OFF_WOR = 9 * HS;
constexpr int OFF_BAR = OFF_WOR + 4 * 2048;
constexpr int SMEM_BYTES = RING + OFF_BAR + 512;
constexpr int OFF_W24 = 0;
constexpr int OTILE = 128 * 144;
constexpr int OFF_OP = OTILE, OFF_WO0 = OTILE + 2048;
constexpr int OFF_AK = 6 * HS, OFF_AQ = OFF_AK + 8960, OFF_AV = 7 * HS;
constexpr int BAR_FULL = 0, BAR_EMPTY = 9, BAR_X = 18, BAR_WOR = 27, BAR_XDONE = 28, BAR_W24 = 29, BAR_QST = 30, BAR_WOF = 31, BAR_WOE = 33,
              BAR_ATI = 35, BAR_ATD = 37, BAR_O = 39, BAR_OFREE = 40;
constexpr uint32_t X_T0 = 330, X_DT = 210, W_T0 = 2100;
constexpr int SPIN_LIMIT = 1 << 20;

__device__ uint4 g_qkv[216 * SEQ];
__device__ uint32_t g_o[128 * 128 * 36];
__device__ unsigned g_cnt[16 * 32];
__device__ unsigned g_done;
__device__ unsigned g_epoch;

__device__ __forceinline__ uint32_t smem_u32(const void* p) { return (uint32_t)__cvta_generic_to_shared(p); }
__device__ __forceinline__ uint32_t clk() { uint32_t c; asm volatile("mov.u32 %0, %%clock;" : "=r"(c)); return c; }
__device__ __forceinline__ void wg_fence() { asm volatile("wgmma.fence.sync.aligned;\n" ::: "memory"); }
__device__ __forceinline__ void wg_commit() { asm volatile("wgmma.commit_group.sync.aligned;\n" ::: "memory"); }
template <int N> __device__ __forceinline__ void wg_wait() { asm volatile("wgmma.wait_group.sync.aligned %0;\n" ::"n"(N) : "memory"); }
__device__ __forceinline__ void mbar_init(uint32_t a, int c) { asm volatile("mbarrier.init.shared::cta.b64 [%0], %1;" ::"r"(a), "r"(c) : "memory"); }
__device__ __forceinline__ void mbar_expect(uint32_t a, uint32_t b) { asm volatile("mbarrier.arrive.expect_tx.shared::cta.b64 _, [%0], %1;" ::"r"(a), "r"(b) : "memory"); }
__device__ __forceinline__ void mbar_arrive(uint32_t a) { asm volatile("mbarrier.arrive.shared::cta.b64 _, [%0];" ::"r"(a) : "memory"); }
__device__ __forceinline__ uint32_t mbar_try(uint32_t a, uint32_t par) {
  uint32_t ok;
  asm volatile("{\n.reg .pred p;\nmbarrier.try_wait.parity.shared::cta.b64 p, [%1], %2;\nselp.u32 %0,1,0,p;\n}\n" : "=r"(ok) : "r"(a), "r"(par) : "memory");
  return ok;
}
__device__ __forceinline__ void mbar_wait(uint32_t a, uint32_t par) {
  int it = 0;
  while (true) {
    if (mbar_try(a, par)) break;
    if (++it > SPIN_LIMIT) __trap();
  }
}
__device__ __forceinline__ void fence_mbar_init() { asm volatile("fence.mbarrier_init.release.cluster;" ::: "memory"); }
__device__ __forceinline__ void fence_async_smem() { asm volatile("fence.proxy.async.shared::cta;\n" ::: "memory"); }
__device__ __forceinline__ void fence_async_gmem() { asm volatile("fence.proxy.async.global;\n" ::: "memory"); }
__device__ __forceinline__ void tma2d(uint32_t dst, const CUtensorMap* m, int c0, int c1, uint32_t bar) {
  asm volatile("cp.async.bulk.tensor.2d.shared::cluster.global.mbarrier::complete_tx::bytes [%0], [%1, {%3, %4}], [%2];" ::"r"(dst), "l"(m), "r"(bar), "r"(c0), "r"(c1) : "memory");
}
__device__ __forceinline__ void bulk_g2s(uint32_t dst, const void* src, uint32_t bytes, uint32_t bar) {
  asm volatile("cp.async.bulk.shared::cluster.global.mbarrier::complete_tx::bytes [%0], [%1], %2, [%3];" ::"r"(dst), "l"(src), "r"(bytes), "r"(bar) : "memory");
}
__device__ __forceinline__ void tma2d_store(const CUtensorMap* m, uint32_t src, int c0, int c1) {
  asm volatile("cp.async.bulk.tensor.2d.global.shared::cta.tile.bulk_group [%0, {%2, %3}], [%1];" ::"l"(m), "r"(src), "r"(c0), "r"(c1) : "memory");
}
__device__ __forceinline__ bool elect() {
  uint32_t p;
  asm volatile("{\n.reg .pred p;\nelect.sync _|p, 0xffffffff;\nselp.u32 %0, 1, 0, p;\n}\n" : "=r"(p));
  return p;
}
__device__ __forceinline__ void tma2d_red(const CUtensorMap* m, uint32_t src, int c0, int c1) {
  asm volatile("cp.reduce.async.bulk.tensor.2d.global.shared::cta.add.tile.bulk_group [%0, {%2, %3}], [%1];" ::"l"(m), "r"(src), "r"(c0), "r"(c1) : "memory");
}
__device__ __forceinline__ void bulk_commit() { asm volatile("cp.async.bulk.commit_group;" ::: "memory"); }
__device__ __forceinline__ void bulk_wait_all() { asm volatile("cp.async.bulk.wait_group 0;" ::: "memory"); }
__device__ __forceinline__ void bulk_wait_read_all() { asm volatile("cp.async.bulk.wait_group.read 0;" ::: "memory"); }
__device__ __forceinline__ void ldsm4(uint32_t addr, uint32_t& r0, uint32_t& r1, uint32_t& r2, uint32_t& r3) {
  asm volatile("ldmatrix.sync.aligned.m8n8.x4.shared.b16 {%0,%1,%2,%3}, [%4];" : "=r"(r0), "=r"(r1), "=r"(r2), "=r"(r3) : "r"(addr) : "memory");
}
__device__ __forceinline__ void ldsm4_tied(uint32_t zero, uint32_t addr, uint32_t& r0, uint32_t& r1, uint32_t& r2, uint32_t& r3) {
  asm volatile("{\n.reg .pred p;\nsetp.eq.u32 p, %5, 0;\n@p ldmatrix.sync.aligned.m8n8.x4.shared.b16 {%0,%1,%2,%3}, [%4];\n}\n"
               : "+r"(r0), "+r"(r1), "+r"(r2), "+r"(r3) : "r"(addr), "r"(zero) : "memory");
}
__device__ __forceinline__ void stsm4(uint32_t addr, uint32_t r0, uint32_t r1, uint32_t r2, uint32_t r3) {
  asm volatile("stmatrix.sync.aligned.m8n8.x4.shared.b16 [%0], {%1,%2,%3,%4};" ::"r"(addr), "r"(r0), "r"(r1), "r"(r2), "r"(r3) : "memory");
}
template <int N> __device__ __forceinline__ void lds(uint32_t addr, uint32_t* v) {
  if (N == 4) asm volatile("ld.shared.v4.b32 {%0,%1,%2,%3}, [%4];" : "=r"(v[0]), "=r"(v[1]), "=r"(v[2]), "=r"(v[3]) : "r"(addr));
  else if (N == 2) asm volatile("ld.shared.v2.b32 {%0,%1}, [%2];" : "=r"(v[0]), "=r"(v[1]) : "r"(addr));
  else asm volatile("ld.shared.b32 %0, [%1];" : "=r"(v[0]) : "r"(addr));
}
__device__ __forceinline__ uint32_t pack2(float lo, float hi) { uint32_t r; asm("cvt.rn.bf16x2.f32 %0, %1, %2;" : "=r"(r) : "f"(hi), "f"(lo)); return r; }
__device__ __forceinline__ float bf_lo(uint32_t v) { return __uint_as_float(v << 16); }
__device__ __forceinline__ float bf_hi(uint32_t v) { return __uint_as_float(v & 0xffff0000u); }
__device__ __forceinline__ uint32_t bsub2(uint32_t a, uint32_t b) { uint32_t r; asm("sub.rn.bf16x2 %0, %1, %2;" : "=r"(r) : "r"(a), "r"(b)); return r; }
__device__ __forceinline__ uint32_t bmul2(uint32_t a, uint32_t b) { uint32_t r; asm("mul.rn.bf16x2 %0, %1, %2;" : "=r"(r) : "r"(a), "r"(b)); return r; }
__device__ __forceinline__ float tanh_hw(float x) { float y; asm("tanh.approx.f32 %0, %1;" : "=f"(y) : "f"(x)); return y; }
__device__ __forceinline__ float ex2(float x) { float y; asm("ex2.approx.ftz.f32 %0, %1;" : "=f"(y) : "f"(x)); return y; }
__device__ __forceinline__ unsigned ld_acquire(const unsigned* p) { unsigned v; asm volatile("ld.acquire.gpu.global.u32 %0, [%1];" : "=r"(v) : "l"(p) : "memory"); return v; }
__device__ __forceinline__ void red_release(unsigned* p, unsigned v) { asm volatile("red.release.gpu.global.add.u32 [%0], %1;" ::"l"(p), "r"(v) : "memory"); }
__device__ __forceinline__ void wait_counter(const unsigned* p, unsigned target) {
  int it = 0;
  while ((int)(ld_acquire(p) - target) < 0) { __nanosleep(128); if (++it > SPIN_LIMIT) __trap(); }
}
__device__ __forceinline__ void mma16816(float (&d)[4], uint32_t a0, uint32_t a1, uint32_t a2, uint32_t a3, uint32_t b0, uint32_t b1) {
  asm volatile("mma.sync.aligned.m16n8k16.row.col.f32.bf16.bf16.f32 {%0,%1,%2,%3}, {%4,%5,%6,%7}, {%8,%9}, {%0,%1,%2,%3};"
               : "+f"(d[0]), "+f"(d[1]), "+f"(d[2]), "+f"(d[3]) : "r"(a0), "r"(a1), "r"(a2), "r"(a3), "r"(b0), "r"(b1));
}
__device__ __forceinline__ void mma1688(float (&d)[4], uint32_t a0, uint32_t a1, uint32_t b0) {
  asm volatile("mma.sync.aligned.m16n8k8.row.col.f32.bf16.bf16.f32 {%0,%1,%2,%3}, {%4,%5}, {%6}, {%0,%1,%2,%3};"
               : "+f"(d[0]), "+f"(d[1]), "+f"(d[2]), "+f"(d[3]) : "r"(a0), "r"(a1), "r"(b0));
}

template <int NA> __device__ __forceinline__ void wgmma_rs_n64(float (&d)[NA], uint32_t a0, uint32_t a1, uint32_t a2, uint32_t a3, uint64_t db, int sd) {
  asm volatile("{\n.reg .pred p;\nsetp.ne.b32 p, %37, 0;\n"
    "wgmma.mma_async.sync.aligned.m64n64k16.f32.bf16.bf16 {%0, %1, %2, %3, %4, %5, %6, %7, %8, %9, %10, %11, %12, %13, %14, %15, %16, %17, %18, %19, %20, %21, %22, %23, %24, %25, %26, %27, %28, %29, %30, %31}, {%32, %33, %34, %35}, %36, p, 1, 1, 1;\n"
    "}\n"
    : "+f"(d[0]), "+f"(d[1]), "+f"(d[2]), "+f"(d[3]), "+f"(d[4]), "+f"(d[5]), "+f"(d[6]), "+f"(d[7]), "+f"(d[8]), "+f"(d[9]), "+f"(d[10]), "+f"(d[11]), "+f"(d[12]), "+f"(d[13]), "+f"(d[14]), "+f"(d[15]), "+f"(d[16]), "+f"(d[17]), "+f"(d[18]), "+f"(d[19]), "+f"(d[20]), "+f"(d[21]), "+f"(d[22]), "+f"(d[23]), "+f"(d[24]), "+f"(d[25]), "+f"(d[26]), "+f"(d[27]), "+f"(d[28]), "+f"(d[29]), "+f"(d[30]), "+f"(d[31])
    : "r"(a0), "r"(a1), "r"(a2), "r"(a3), "l"(db), "r"(sd));
}

template <int NA> __device__ __forceinline__ void wgmma_ss_n64(float (&d)[NA], uint64_t da, uint64_t db, int sd) {
  asm volatile("{\n.reg .pred p;\nsetp.ne.b32 p, %34, 0;\n"
    "wgmma.mma_async.sync.aligned.m64n64k16.f32.bf16.bf16 {%0, %1, %2, %3, %4, %5, %6, %7, %8, %9, %10, %11, %12, %13, %14, %15, %16, %17, %18, %19, %20, %21, %22, %23, %24, %25, %26, %27, %28, %29, %30, %31}, %32, %33, p, 1, 1, 0, 1;\n"
    "}\n"
    : "+f"(d[0]), "+f"(d[1]), "+f"(d[2]), "+f"(d[3]), "+f"(d[4]), "+f"(d[5]), "+f"(d[6]), "+f"(d[7]), "+f"(d[8]), "+f"(d[9]), "+f"(d[10]), "+f"(d[11]), "+f"(d[12]), "+f"(d[13]), "+f"(d[14]), "+f"(d[15]), "+f"(d[16]), "+f"(d[17]), "+f"(d[18]), "+f"(d[19]), "+f"(d[20]), "+f"(d[21]), "+f"(d[22]), "+f"(d[23]), "+f"(d[24]), "+f"(d[25]), "+f"(d[26]), "+f"(d[27]), "+f"(d[28]), "+f"(d[29]), "+f"(d[30]), "+f"(d[31])
    : "l"(da), "l"(db), "r"(sd));
}

template <int NA> __device__ __forceinline__ void wgmma_rs_n88(float (&d)[NA], uint32_t a0, uint32_t a1, uint32_t a2, uint32_t a3, uint64_t db, int sd) {
  asm volatile("{\n.reg .pred p;\nsetp.ne.b32 p, %49, 0;\n"
    "wgmma.mma_async.sync.aligned.m64n88k16.f32.bf16.bf16 {%0, %1, %2, %3, %4, %5, %6, %7, %8, %9, %10, %11, %12, %13, %14, %15, %16, %17, %18, %19, %20, %21, %22, %23, %24, %25, %26, %27, %28, %29, %30, %31, %32, %33, %34, %35, %36, %37, %38, %39, %40, %41, %42, %43}, {%44, %45, %46, %47}, %48, p, 1, 1, 1;\n"
    "}\n"
    : "+f"(d[0]), "+f"(d[1]), "+f"(d[2]), "+f"(d[3]), "+f"(d[4]), "+f"(d[5]), "+f"(d[6]), "+f"(d[7]), "+f"(d[8]), "+f"(d[9]), "+f"(d[10]), "+f"(d[11]), "+f"(d[12]), "+f"(d[13]), "+f"(d[14]), "+f"(d[15]), "+f"(d[16]), "+f"(d[17]), "+f"(d[18]), "+f"(d[19]), "+f"(d[20]), "+f"(d[21]), "+f"(d[22]), "+f"(d[23]), "+f"(d[24]), "+f"(d[25]), "+f"(d[26]), "+f"(d[27]), "+f"(d[28]), "+f"(d[29]), "+f"(d[30]), "+f"(d[31]), "+f"(d[32]), "+f"(d[33]), "+f"(d[34]), "+f"(d[35]), "+f"(d[36]), "+f"(d[37]), "+f"(d[38]), "+f"(d[39]), "+f"(d[40]), "+f"(d[41]), "+f"(d[42]), "+f"(d[43])
    : "r"(a0), "r"(a1), "r"(a2), "r"(a3), "l"(db), "r"(sd));
}

template <int NA> __device__ __forceinline__ void wgmma_ss_n88(float (&d)[NA], uint64_t da, uint64_t db, int sd) {
  asm volatile("{\n.reg .pred p;\nsetp.ne.b32 p, %46, 0;\n"
    "wgmma.mma_async.sync.aligned.m64n88k16.f32.bf16.bf16 {%0, %1, %2, %3, %4, %5, %6, %7, %8, %9, %10, %11, %12, %13, %14, %15, %16, %17, %18, %19, %20, %21, %22, %23, %24, %25, %26, %27, %28, %29, %30, %31, %32, %33, %34, %35, %36, %37, %38, %39, %40, %41, %42, %43}, %44, %45, p, 1, 1, 0, 1;\n"
    "}\n"
    : "+f"(d[0]), "+f"(d[1]), "+f"(d[2]), "+f"(d[3]), "+f"(d[4]), "+f"(d[5]), "+f"(d[6]), "+f"(d[7]), "+f"(d[8]), "+f"(d[9]), "+f"(d[10]), "+f"(d[11]), "+f"(d[12]), "+f"(d[13]), "+f"(d[14]), "+f"(d[15]), "+f"(d[16]), "+f"(d[17]), "+f"(d[18]), "+f"(d[19]), "+f"(d[20]), "+f"(d[21]), "+f"(d[22]), "+f"(d[23]), "+f"(d[24]), "+f"(d[25]), "+f"(d[26]), "+f"(d[27]), "+f"(d[28]), "+f"(d[29]), "+f"(d[30]), "+f"(d[31]), "+f"(d[32]), "+f"(d[33]), "+f"(d[34]), "+f"(d[35]), "+f"(d[36]), "+f"(d[37]), "+f"(d[38]), "+f"(d[39]), "+f"(d[40]), "+f"(d[41]), "+f"(d[42]), "+f"(d[43])
    : "l"(da), "l"(db), "r"(sd));
}


__device__ __forceinline__ uint64_t mkd(uint32_t lo) { return ((uint64_t)0x40000040u << 32) | (uint64_t)lo; }

constexpr uint32_t sr = 1024, sb = sr + RING;
constexpr uint32_t bars = sb + OFF_BAR;
constexpr uint32_t RING_LO = (sr >> 4) | (512u << 16);

template <int NA> __device__ __forceinline__ void acc_fence(float (&d)[NA]) {
  asm volatile("" : "+f"(d[0]), "+f"(d[1]), "+f"(d[2]), "+f"(d[3]), "+f"(d[4]), "+f"(d[5]), "+f"(d[6]), "+f"(d[7]), "+f"(d[8]), "+f"(d[9]), "+f"(d[10]), "+f"(d[11]), "+f"(d[12]), "+f"(d[13]), "+f"(d[14]), "+f"(d[15]), "+f"(d[16]), "+f"(d[17]), "+f"(d[18]), "+f"(d[19]), "+f"(d[20]), "+f"(d[21]), "+f"(d[22]), "+f"(d[23]), "+f"(d[24]), "+f"(d[25]), "+f"(d[26]), "+f"(d[27]), "+f"(d[28]), "+f"(d[29]), "+f"(d[30]), "+f"(d[31]) :: "memory");
}

template <int V> struct IC { static constexpr int value = V; };

__device__ constexpr bool x_in_smem(int kb, int kk) { return (kb & 1) && kk == 3; }
__device__ constexpr int x_reg(int kb, int kk) { return (4 * kb + kk - (kb >> 1)) * 4; }
__device__ constexpr bool h_in_smem(int kb, int kk) { return kb >= 4 && kb < 8 && (kk & 1); }
__device__ constexpr int h_reg(int kb, int kk) { return (kb < 4 ? 4 * kb + kk : kb < 8 ? 8 + 2 * kb + (kk >> 1) : 4 * kb - 8 + kk) * 4; }

template <int PH, bool FIRST, int NA, class M, class F>
__device__ __forceinline__ void run_pass(float (&other)[NA], M&& mma, F&& slice) {
#pragma unroll
  for (int s = 0; s < 9; s++) {
    wg_fence();
    mma(s, RING_LO + s * (SLOT >> 4));
    wg_commit();
    mbar_wait(bars + (BAR_FULL + (s + 1) % 9) * 8, s < 8 ? PH : PH ^ 1);
    slice(s);
    wg_wait<1>();
    if (s == 0) acc_fence(other);
    if ((s || !FIRST) && (threadIdx.x & 127) == 0) mbar_arrive(bars + (BAR_EMPTY + (s + 8) % 9) * 8);
  }
}

template <int BUF, int PH, bool FIRST, int NA, class M, class F>
__device__ __forceinline__ void run_down(uint32_t wpar, bool last, float (&other)[NA], M&& mma, F&& slice) {
#pragma unroll
  for (int s = 0; s < 10; s++) {
    wg_fence();
    mma(s, s < 9 ? RING_LO + s * (SLOT >> 4) : ((sb + 8 * HS + BUF * SLOT) >> 4) | (512u << 16));
    wg_commit();
    if (s < 8) mbar_wait(bars + (BAR_FULL + s + 1) * 8, PH);
    else if (s == 8) mbar_wait(bars + (BAR_WOF + BUF) * 8, wpar);
    else if (!last) mbar_wait(bars + BAR_FULL * 8, PH ^ 1);
    slice(s);
    wg_wait<1>();
    if (s == 0) acc_fence(other);
    if ((threadIdx.x & 127) == 0) {
      if (s) mbar_arrive(bars + (BAR_EMPTY + s - 1) * 8);
      else {
        if (FIRST) { mbar_arrive(bars + (BAR_EMPTY + 8) * 8); mbar_arrive(bars + (BAR_WOE + BUF) * 8); }
        mbar_arrive(bars + (BAR_WOE + (BUF ^ 1)) * 8);
      }
    }
  }
}

struct Maps {
  CUtensorMap x, wqkv, w24, wg, wu, wd, woa, wob, out, lkv, lq, op;
};

__global__ void __launch_bounds__(384, 1)
fused_kernel(uint32_t zero, const __grid_constant__ Maps mp) {
  extern __shared__ __align__(1024) uint8_t smem[];
  const int j = (blockIdx.x >> 2) & 7, m = (blockIdx.x & 3) + ((blockIdx.x >> 3) & 12);
  const int m0 = m * 128;
  const uint32_t t0 = clk();
  auto load_x = [&](int i) {
    mbar_expect(bars + (BAR_X + i) * 8, HS);
    if (i) while (clk() - t0 < X_T0 + i * X_DT) {}
    tma2d(sb + i * HS, &mp.x, i * 64, m0, bars + (BAR_X + i) * 8);
  };
  if (threadIdx.x == 256) {
#pragma unroll
    for (int i = 0; i < 2; i++) {
      mbar_init(bars + (BAR_X + i) * 8, 1);
      fence_mbar_init();
      load_x(i);
    }
  }
  const int warp = __shfl_sync(0xffffffffu, threadIdx.x >> 5, 0), lane = threadIdx.x & 31;

  if (warp < 8) {
    asm volatile("bar.sync 0, 384;" ::: "memory");
    asm volatile("setmaxnreg.inc.sync.aligned.u32 232;\n");
    const int wg = warp >> 2;
    const int lrow = (warp & 3) * 16 + (lane & 15);
    const uint32_t rowa = sb + wg * 8192 + lrow * 128;
    const uint32_t swz = ((lane >> 4) ^ (lrow & 7)) << 4;
    uint32_t adr[4];
#pragma unroll
    for (int i = 0; i < 4; i++) { adr[i] = rowa + (swz ^ (i << 5)); asm volatile("" : "+r"(adr[i])); }
    uint32_t a[128];
    uint32_t sg[16], oq[4], oz[4];
    float accA[32], accB[44];
    float rs0, rs1, rh0, rh1;
    uint32_t mp0, mp1;
    auto xq = [&](int kb, int kk) { return x_in_smem(kb, kk) ? &sg[(kb >> 1) * 4] : &a[x_reg(kb, kk)]; };
    {
      float cs[2][4] = {}, c1[2][4] = {}, c2[2][4] = {};
      mbar_wait(bars + BAR_X * 8, 0);
#pragma unroll
      for (int kb = 0; kb < 9; kb++) {
        uint32_t ok = 1;
        if (kb < 8) ok = mbar_try(bars + (BAR_X + kb + 1) * 8, 0);
#pragma unroll
        for (int kk = 0; kk < 4; kk++) {
          uint32_t* r = xq(kb, kk);
          ldsm4(adr[kk] + kb * HS, r[0], r[1], r[2], r[3]);
        }
#pragma unroll
        for (int kk = 0; kk < 4; kk++) {
          const uint32_t* r = xq(kb, kk);
          mma16816(cs[kk & 1], r[0], r[1], r[2], r[3], 0x3f803f80u, 0x3f803f80u);
          mma1688(c1[0], r[0], r[1], r[0]);
          mma1688(c2[0], r[0], r[1], r[1]);
          mma1688(c1[1], r[2], r[3], r[2]);
          mma1688(c2[1], r[2], r[3], r[3]);
        }
        if (!ok) mbar_wait(bars + (BAR_X + kb + 1) * 8, 0);
      }
      __syncwarp();
      if (lane == 0) mbar_arrive(bars + BAR_XDONE * 8);
      const float mu0 = (cs[0][0] + cs[1][0]) * (1.f / DM), mu1 = (cs[0][2] + cs[1][2]) * (1.f / DM);
      mp0 = pack2(mu0, mu0); mp1 = pack2(mu1, mu1);
      rs0 = (lane & 4) ? c1[0][1] + c1[1][1] : c1[0][0] + c1[1][0];
      rs1 = (lane & 4) ? c2[0][3] + c2[1][3] : c2[0][2] + c2[1][2];
      rh0 = mu0 * mu0; rh1 = mu1 * mu1;
    }
    auto finish_rstd = [&]() {
      const int src = (lane & ~3) | (lane >> 3);
      rs0 = rsqrtf(fmaxf(__shfl_sync(0xffffffffu, rs0, src) * (1.f / DM) - rh0, 0.f) + 1e-5f);
      rs1 = rsqrtf(fmaxf(__shfl_sync(0xffffffffu, rs1, src) * (1.f / DM) - rh1, 0.f) + 1e-5f);
      rh0 = 0.5f * rs0; rh1 = 0.5f * rs1;
    };
    auto centre = [&](int kb) {
#pragma unroll
      for (int i = 0; i < 16; i++) { uint32_t& v = xq(kb, i >> 2)[i & 3]; v = bsub2(v, (i & 1) ? mp1 : mp0); }
    };
    centre(0);

    const uint32_t xlo = ((sb + 8 * HS + wg * 8192) >> 4) | (1u << 16);

    auto mma64 = [&](auto& acc, int s, uint32_t blo) {
#pragma unroll
      for (int kk = 0; kk < 4; kk++) {
        const uint32_t* r = &a[x_reg(s, kk)];
        if (x_in_smem(s, kk)) wgmma_ss_n64(acc, mkd(xlo + (s >> 1) * 2), mkd(blo + kk * 128), 1);
        else wgmma_rs_n64(acc, r[0], r[1], r[2], r[3], mkd(blo + kk * 128), s || kk);
      }
    };
    char* qp = reinterpret_cast<char*>(g_qkv + (j * 24) * SEQ + m0 + (threadIdx.x >> 5) * 16) + (threadIdx.x & 31) * 4;
    auto qkv_store = [&](const auto& acc, int nb, int chunk) {
      *reinterpret_cast<uint32_t*>(qp + chunk * (SEQ * 16)) = pack2(acc[4 * nb] * rs0, acc[4 * nb + 1] * rs0);
      *reinterpret_cast<uint32_t*>(qp + chunk * (SEQ * 16) + 128) = pack2(acc[4 * nb + 2] * rs1, acc[4 * nb + 3] * rs1);
    };
    auto sig_slice = [&](const auto& acc, int s) {
      if (s >= 1) {
#pragma unroll
        for (int e = 2 * (s - 1); e < 2 * s; e++) {
          const float r = (e & 1) ? rh1 : rh0;
          sg[e] = pack2(fmaf(tanh_hw(acc[2 * e] * r), r, r), fmaf(tanh_hw(acc[2 * e + 1] * r), r, r));
        }
      }
    };
    auto h_val = [&](const auto& acc, int e) { return bmul2(sg[e], pack2(acc[2 * e], acc[2 * e + 1])); };
    auto load_h = [&](int pos) {
#pragma unroll
      for (int i = 0; i < 2; i++) {
        const int kb = pos < 8 ? pos >> 1 : pos - 4, kk = pos < 8 ? (pos & 1) * 2 + i : 2 * i;
        uint32_t* r = &a[h_reg(kb, kk)];
        ldsm4_tied(zero, adr[kk] + kb * HS, r[0], r[1], r[2], r[3]);
      }
    };

    mbar_wait(bars + BAR_FULL * 8, 0);
    run_pass<0, true>(accA, [&](int s, uint32_t b) {
#pragma unroll
      for (int kk = 0; kk < 4; kk++) {
        const uint32_t* r = xq(s, kk);
        wgmma_rs_n64(accB, r[0], r[1], r[2], r[3], mkd(b + kk * 128), s || kk);
      }
    }, [&](int s) {
      if (s < 8) centre(s + 1);
      if (s == 0) finish_rstd();
      if (s == 7) {
        mbar_wait(bars + BAR_XDONE * 8, 0);
#pragma unroll
        for (int kk = 0; kk < 4; kk++) stsm4(adr[kk] + 8 * HS, sg[kk * 4], sg[kk * 4 + 1], sg[kk * 4 + 2], sg[kk * 4 + 3]);
        fence_async_smem();
      }
      if (s == 8) asm volatile("bar.sync %0, 128;" ::"r"(1 + wg) : "memory");
    });
    run_pass<1, false>(accB, [&](int s, uint32_t b) { mma64(accA, s, b); }, [&](int s) {
      if (s >= 1) qkv_store(accB, s - 1, s - 1);
      if (s == 8) mbar_wait(bars + BAR_W24 * 8, 0);
    });
    run_pass<0, false>(accA, [&](int s, uint32_t b) {
      const uint32_t lo = (b & 0xffffu) | (((OFF_W24 + RING) >> 4) << 16);
#pragma unroll
      for (int kk = 0; kk < 4; kk++) {
        const uint32_t* r = &a[x_reg(s, kk)];
        if (x_in_smem(s, kk)) wgmma_ss_n88(accB, mkd(xlo + (s >> 1) * 2), mkd(lo + kk * 128), 1);
        else wgmma_rs_n88(accB, r[0], r[1], r[2], r[3], mkd(lo + kk * 128), s || kk);
      }
    }, [&](int s) { if (s >= 1) qkv_store(accA, s - 1, 7 + s); });
    run_pass<1, false>(accB, [&](int s, uint32_t b) { mma64(accA, s, b); }, [&](int s) {
      if (s == 1) asm volatile("" : "+f"(accB[32]), "+f"(accB[33]), "+f"(accB[34]), "+f"(accB[35]), "+f"(accB[36]), "+f"(accB[37]), "+f"(accB[38]),
                               "+f"(accB[39]), "+f"(accB[40]), "+f"(accB[41]), "+f"(accB[42]), "+f"(accB[43]) :: "memory");
      if (s >= 1 && s <= 4) { qkv_store(accB, 2 * s - 2, 14 + 2 * s); qkv_store(accB, 2 * s - 1, 15 + 2 * s); }
      if (s == 5) { qp += (192 - 21 * j) * (SEQ * 16); qkv_store(accB, 8, 0); qkv_store(accB, 9, 1); }
      if (s == 6) {
        qkv_store(accB, 10, 2);
        __syncwarp();
        if (lane == 0) mbar_arrive(bars + BAR_QST * 8);
      }
    });
    for (int c = 0; c < 8; c++) {
      run_pass<0, false>(accA, [&](int s, uint32_t b) { mma64(accB, s, b); }, [&](int s) { sig_slice(accA, s); });
      run_pass<1, false>(accB, [&](int s, uint32_t b) { mma64(accA, s, b); }, [&](int s) {
        if (s == 1 && c >= 6) mbar_wait(bars + (BAR_ATD - 6 + c) * 8, 0);
        if (s >= 1 && s <= 7 && (s & 1)) {
          const int t = s >> 1;
          stsm4(adr[t] + c * HS, h_val(accB, 4 * t), h_val(accB, 4 * t + 1), h_val(accB, 4 * t + 2), h_val(accB, 4 * t + 3));
        }
      });
    }
    run_pass<0, false>(accA, [&](int s, uint32_t b) { mma64(accB, s, b); }, [&](int s) {
      sig_slice(accA, s);
      if (s == 0) {
        fence_async_smem();
        asm volatile("bar.sync %0, 128;" ::"r"(1 + wg) : "memory");
      }
      if (s >= 2) load_h(s - 2);
      if (s == 6) {
        __syncwarp();
        if (lane == 0) mbar_arrive(bars + BAR_OFREE * 8);
      }
    });
    constexpr uint32_t worlo = ((sb + OFF_WOR) >> 4) | (512u << 16);
    const int grow = m0 + warp * 16;
    int blk = j;
    auto mmaD = [&](auto& acc, int s, uint32_t blo, const uint32_t* sh, uint32_t shlo) {
#pragma unroll
      for (int kk = 0; kk < 4; kk++) {
        const uint32_t* r = &a[h_reg(s, kk)];
        if (h_in_smem(s, kk)) wgmma_ss_n64(acc, mkd(xlo - (8 - s) * (HS >> 4) + kk * 2), mkd(blo + kk * 128), 1);
        else wgmma_rs_n64(acc, r[0], r[1], r[2], r[3], mkd(blo + kk * 128), s || kk);
      }
      if (s == 9 && sh) wgmma_rs_n64(acc, sh[0], sh[1], sh[2], sh[3], mkd(shlo), 1);
    };
    auto flush_store = [&](const auto& acc, int slot, int t) {
      stsm4(adr[t] + slot * HS, pack2(acc[8 * t], acc[8 * t + 1]), pack2(acc[8 * t + 2], acc[8 * t + 3]),
            pack2(acc[8 * t + 4], acc[8 * t + 5]), pack2(acc[8 * t + 6], acc[8 * t + 7]));
    };
    auto flush_issue = [&](int slot, int cb) {
      fence_async_smem();
      __syncwarp();
      if (elect()) { tma2d_red(&mp.out, sb + slot * HS + warp * 2048, cb * 64, grow); bulk_commit(); }
    };
    run_down<0, 1, true>(0, false, accB, [&](int s, uint32_t b) { mmaD(accA, s, b, oz, ((sb + OFF_WO0) >> 4) | (512u << 16)); }, [&](int s) {
      if (s < 5) load_h(7 + s);
      if (s >= 1 && s <= 4) {
#pragma unroll
        for (int e = 4 * (s - 1); e < 4 * s; e++) a[96 + e] = h_val(accB, e);
      }
      if (s == 7) {
        mbar_wait(bars + BAR_WOR * 8, 0);
        mbar_wait(bars + BAR_O * 8, 0);
        fence_async_gmem();
        const uint32_t orow = (threadIdx.x >> 5) * 16 + (threadIdx.x & 15), oa = sb + orow * 144, odd = j & 1;
#pragma unroll
        for (int kk = 0; kk < 4; kk++) ldsm4(oa + odd * 16 + kk * 32 + (threadIdx.x & 16), a[112 + kk * 4], a[113 + kk * 4], a[114 + kk * 4], a[115 + kk * 4]);
        ldsm4(((threadIdx.x >> 4) & 1) == odd ? oa + 128 - odd * 128 : sb + OFF_OP + orow * 16, oq[0], oq[1], oq[2], oq[3]);
#pragma unroll
        for (int i = 0; i < 4; i++) asm volatile("mul.lo.u32 %0, %1, %2;" : "=r"(oz[i]) : "r"(oq[i]), "r"(odd ^ 1));
      }
    });
    auto flush_slice = [&](const auto& acc, int slot, int cb, int s) {
      if (s == 0) { asm volatile("cp.async.bulk.wait_group.read 1;" ::: "memory"); __syncwarp(); }
      if (s >= 1 && s <= 4) flush_store(acc, slot, s - 1);
      if (s == 5) flush_issue(slot, cb);
    };
    for (int p = 1; p < 9; p += 2) {
      int pb = blk; blk = (blk == 8) ? 0 : blk + 1;
      run_down<1, 0, false>((p >> 1) & 1, false, accA, [&](int s, uint32_t b) { mmaD(accB, s, b, oq, worlo + (p >> 1) * 128); }, [&](int s) { flush_slice(accA, 2, pb, s); });
      pb = blk; blk = (blk == 8) ? 0 : blk + 1;
      if (p == 7 && wg == 1) asm volatile("bar.sync 5, 256;" ::: "memory");
      run_down<0, 1, false>(((p + 1) >> 1) & 1, p == 7, accB, [&](int s, uint32_t b) { mmaD(accA, s, b, nullptr, 0); }, [&](int s) {
        flush_slice(accB, 3, pb, s);
        if (s == 3 && p == 7 && wg == 0) asm volatile("bar.arrive 5, 256;" ::: "memory");
      });
    }
    flush_slice(accA, 2, blk, 0);
    wg_wait<0>();
    acc_fence(accA);
#pragma unroll
    for (int t = 1; t <= 5; t++) flush_slice(accA, 2, blk, t);
    bulk_wait_read_all();
  } else {
    asm volatile("setmaxnreg.dec.sync.aligned.u32 40;\n");
    if (warp == 8) {
      asm volatile("bar.sync 0, 384;" ::: "memory");
      while (clk() - t0 < W_T0) {}
      int st = 0; uint32_t ph = 1;
      auto stage = [&](const CUtensorMap* w, int c0, int c1) {
        mbar_wait(bars + (BAR_EMPTY + st) * 8, ph);
        const uint32_t fb = bars + (BAR_FULL + st) * 8;
        if (elect()) {
          mbar_expect(fb, SLOT);
          tma2d(sr + st * SLOT, w, c0, c1, fb);
        }
        st++;
        if (st == NSLOT) { st = 0; ph ^= 1; }
      };
      int blk = j;
#pragma unroll 1
      for (int p = 0; p < 30; p++) {
        const CUtensorMap* w; int c0, c1 = 0;
        if (p < 3) { w = &mp.wqkv; c0 = j * 192 + p * 64; }
        else if (p < 21) { w = (p & 1) ? &mp.wg : &mp.wu; c0 = j * 576 + ((p - 3) >> 1) * 64; }
        else { w = &mp.wd; c0 = blk * 64; c1 = j * 576; }
#pragma unroll 1
        for (int kb = 0; kb < 9; kb++) {
          stage(w, c0, c1 + kb * 64);
        }
        if (p >= 21) {
          const int q = p - 21;
          mbar_wait(bars + (BAR_WOE + (q & 1)) * 8, (q >> 1) & 1);
          if (elect()) {
            mbar_expect(bars + (BAR_WOF + (q & 1)) * 8, SLOT);
            tma2d(sb + 8 * HS + (q & 1) * SLOT, &mp.woa, c0, j * 72 + (j & 1) * 8, bars + (BAR_WOF + (q & 1)) * 8);
          }
          blk = (blk == 8) ? 0 : blk + 1;
        }
      }
    } else {
      const int aw = warp - 9;
      if (aw == 0) {
        if (lane == 0) {
          for (int i = 2; i < 9; i++) mbar_init(bars + (BAR_X + i) * 8, 1);
          fence_mbar_init();
        }
        __syncwarp();
        asm volatile("bar.arrive 0, 384;" ::: "memory");
        if (elect()) {
#pragma unroll 1
          for (int i = 2; i < 9; i++) load_x(i);
        }
        __syncwarp();
      } else {
        if (lane == 0) {
          if (aw == 1) {
            if (smem_u32(smem) != sr) __trap();
            for (int i = 0; i < NSLOT; i++) { mbar_init(bars + (BAR_FULL + i) * 8, 1); mbar_init(bars + (BAR_EMPTY + i) * 8, 2); }
          } else {
            mbar_init(bars + BAR_WOR * 8, 1);
            mbar_init(bars + BAR_XDONE * 8, 9);
            mbar_init(bars + BAR_W24 * 8, 1);
            mbar_init(bars + BAR_QST * 8, 8);
            for (int i = 0; i < 2; i++) { mbar_init(bars + (BAR_WOF + i) * 8, 1); mbar_init(bars + (BAR_WOE + i) * 8, 2); }
            for (int i = 0; i < 2; i++) { mbar_init(bars + (BAR_ATI + i) * 8, 1); mbar_init(bars + (BAR_ATD + i) * 8, 1); }
            mbar_init(bars + BAR_O * 8, 1);
            mbar_init(bars + BAR_OFREE * 8, 8);
          }
          fence_mbar_init();
        }
        __syncwarp();
        asm volatile("bar.sync 0, 384;" ::: "memory");
      }
      if (aw == 2 && elect()) {
        const CUtensorMap* mm = &mp.w24;
#pragma unroll 1
        for (int i = 0; i < 10; i++) asm volatile("prefetch.tensormap [%0];" ::"l"(mm + i) : "memory");
      }
      const unsigned target = (*(volatile unsigned*)&g_epoch + 1) * 8;
      if (aw == 1) {
#pragma unroll 1
        for (int kb = 0; kb < 9; kb++) {
          mbar_wait(bars + (BAR_X + kb) * 8, 0);
          if (elect()) tma2d_store(&mp.out, sb + kb * HS + j * 2048, kb * 64, m0 + j * 16);
        }
        if (elect()) bulk_commit();
        bulk_wait_read_all();
        __syncwarp();
        if (lane == 0) mbar_arrive(bars + BAR_XDONE * 8);
      }
      if (aw == 2) {
        mbar_wait(bars + BAR_XDONE * 8, 0);
        if (elect()) { mbar_expect(bars + BAR_W24 * 8, 9 * 64 * 48); mbar_expect(bars + BAR_WOR * 8, 4 * 2048); }
#pragma unroll 1
        for (int b = 0; b < 13; b++) {
          if (elect()) {
            if (b < 9) tma2d(sb + OFF_W24 + b * SLOT, &mp.w24, 1536 + j * 24, b * 64, bars + BAR_W24 * 8);
            else tma2d(sb + OFF_WOR + (b - 9) * 2048, &mp.wob, ((j + 2 * b - 17) % 9) * 64, (j & ~1) * 72 + 64, bars + BAR_WOR * 8);
          }
          __nanosleep(64);
        }
      }
      if (aw == 1) bulk_wait_all();
      asm volatile("bar.sync 3, 96;" ::: "memory");
      auto load_kq = [&](int t) {
        const int r2 = (m0 + t * 48) * 2;
        mbar_expect(bars + BAR_ATI * 8, 9 * (62 + 50) * 16);
        tma2d(sb + OFF_AK, &mp.lkv, r2 - 28, 72 + j * 9, bars + BAR_ATI * 8);
        tma2d(sb + OFF_AQ, &mp.lq, r2, j * 9, bars + BAR_ATI * 8);
      };
      auto load_v = [&](int t) {
        mbar_expect(bars + (BAR_ATI + 1) * 8, 9 * 62 * 16);
        tma2d(sb + OFF_AV, &mp.lkv, (m0 + t * 48) * 2 - 28, 144 + j * 9, bars + (BAR_ATI + 1) * 8);
      };
      if (aw == 0) {
        mbar_wait(bars + BAR_QST * 8, 0);
        if (lane == 0) red_release(&g_cnt[m * 32], 1);
        if (lane < 2) wait_counter(&g_cnt[(lane && m ? m - 1 : m) * 32], target);
        __syncwarp();
        fence_async_gmem();
        if (elect()) { load_kq(0); load_v(0); }
      }
      uint32_t l16 = (aw * 16 + (lane & 1) + (lane & 2) * 2 + (lane >> 4) * 8) * 16;
      auto fresh = [&]() { asm volatile("" : "+r"(l16)); return l16; };
      const float sc = 0.23570226039551584f * 1.4426950408889634f;
#pragma unroll 1
      for (int t = 0; t < 3; t++) {
        const bool active = t < 2 || aw < 2;
        float p0[8] = {}, p1[8] = {};
        uint32_t h8 = (threadIdx.x & 12) * 2;
        asm volatile("" : "+r"(h8));
        const uint32_t po = (0x70482800u >> h8) & 255, po3 = (0x6C682420u >> h8) & 255;
        const uint32_t px = (0x00100000u >> h8) & 255;
        mbar_wait(bars + BAR_ATI * 8, t & 1);
        if (active) {
          auto qk = [&](auto nw, uint32_t b) {
            constexpr int N = decltype(nw)::value;
            uint32_t u[N]; float q0[2 * N], q1[2 * N];
            const uint32_t o = fresh() + (b & 15), qa = o + (b >> 4) * 800 + (sb + OFF_AQ), ka = o + (b >> 4) * 992 + (sb + OFF_AK);
            lds<N>(qa, u);
#pragma unroll
            for (int i = 0; i < N; i++) { q0[2 * i] = bf_lo(u[i]); q0[2 * i + 1] = bf_hi(u[i]); }
            lds<N>(qa + 32, u);
#pragma unroll
            for (int i = 0; i < N; i++) { q1[2 * i] = bf_lo(u[i]); q1[2 * i + 1] = bf_hi(u[i]); }
#pragma unroll
            for (int s = 0; s < 9; s++) {
              lds<N>(ka + (16 - 2 * s) * 16, u);
#pragma unroll
              for (int i = 0; i < N; i++) {
                const float lo = bf_lo(u[i]), hi = bf_hi(u[i]);
                if (s < 8) { p1[s] = fmaf(q1[2 * i], lo, p1[s]); p1[s] = fmaf(q1[2 * i + 1], hi, p1[s]); }
                if (s > 0) { p0[s - 1] = fmaf(q0[2 * i], lo, p0[s - 1]); p0[s - 1] = fmaf(q0[2 * i + 1], hi, p0[s - 1]); }
              }
            }
          };
#pragma unroll 1
          for (int i = 0; i < 4; i++) qk(IC<2>(), po + ((8 * i) ^ px));
          qk(IC<1>(), po3);
        }
        asm volatile("bar.sync 3, 96;" ::: "memory");
        if (aw == 0 && elect()) { if (t < 2) load_kq(t + 1); else mbar_arrive(bars + BAR_ATD * 8); }
        if (active) {
          if (m0 + t == 0) {
            const int row = fresh() >> 4;
#pragma unroll
            for (int w = 1; w < 8; w++) { if (row < 2 * w) p0[w] = -INFINITY; if (row + 2 < 2 * w) p1[w] = -INFINITY; }
          }
          auto softmax = [&](float (&p)[8]) {
            const float mx = fmaxf(fmaxf(fmaxf(p[0], p[1]), fmaxf(p[2], p[3])), fmaxf(fmaxf(p[4], p[5]), fmaxf(p[6], p[7])));
            float l = 0.f;
#pragma unroll
            for (int w = 0; w < 8; w++) { p[w] = ex2((p[w] - mx) * sc); l += p[w]; }
            l = __fdividef(1.f, l);
#pragma unroll
            for (int w = 0; w < 8; w++) p[w] *= l;
          };
          softmax(p0); softmax(p1);
        }
        mbar_wait(bars + (BAR_ATI + 1) * 8, t & 1);
        if (active) {
          char* op = reinterpret_cast<char*>(g_o + (blockIdx.x * 128 + t * 48) * 36) + fresh() * 9;
          auto pv = [&](auto nw, uint32_t b) {
            constexpr int N = decltype(nw)::value;
            uint32_t u[N]; float o0[2 * N] = {}, o1[2 * N] = {};
            const uint32_t va = fresh() + (b & 15) + (b >> 4) * 992 + (sb + OFF_AV);
#pragma unroll
            for (int s = 0; s < 9; s++) {
              lds<N>(va + (16 - 2 * s) * 16, u);
#pragma unroll
              for (int i = 0; i < N; i++) {
                const float lo = bf_lo(u[i]), hi = bf_hi(u[i]);
                if (s < 8) { o1[2 * i] = fmaf(p1[s], lo, o1[2 * i]); o1[2 * i + 1] = fmaf(p1[s], hi, o1[2 * i + 1]); }
                if (s > 0) { o0[2 * i] = fmaf(p0[s - 1], lo, o0[2 * i]); o0[2 * i + 1] = fmaf(p0[s - 1], hi, o0[2 * i + 1]); }
              }
            }
            if (N == 2) {
              *reinterpret_cast<uint2*>(op + b) = make_uint2(pack2(o0[0], o0[1]), pack2(o0[2 % (2 * N)], o0[3 % (2 * N)]));
              *reinterpret_cast<uint2*>(op + b + 288) = make_uint2(pack2(o1[0], o1[1]), pack2(o1[2 % (2 * N)], o1[3 % (2 * N)]));
            } else {
              *reinterpret_cast<uint32_t*>(op + b) = pack2(o0[0], o0[1]);
              *reinterpret_cast<uint32_t*>(op + b + 288) = pack2(o1[0], o1[1]);
            }
          };
#pragma unroll 1
          for (int i = 0; i < 4; i++) pv(IC<2>(), po + ((8 * i) ^ px));
          pv(IC<1>(), po3);
        }
        asm volatile("bar.sync 3, 96;" ::: "memory");
        if (aw == 0 && elect()) { if (t < 2) load_v(t + 1); else mbar_arrive(bars + (BAR_ATD + 1) * 8); }
      }
      if (aw == 0) {
        if (elect()) {
          red_release(&g_cnt[m * 32 + 8 + (j >> 1)], 1);
          wait_counter(&g_cnt[m * 32 + 8 + (j >> 1)], (*(volatile unsigned*)&g_epoch + 1) * 2);
        }
        __syncwarp();
        mbar_wait(bars + BAR_OFREE * 8, 0);
        fence_async_gmem();
        if (elect()) {
          mbar_expect(bars + BAR_O * 8, OTILE + 4096);
          bulk_g2s(sb, g_o + blockIdx.x * 128 * 36, OTILE, bars + BAR_O * 8);
          tma2d(sb + OFF_OP, &mp.op, (j & 1) * 16, (blockIdx.x ^ 4) * 128, bars + BAR_O * 8);
          tma2d(sb + OFF_WO0, &mp.wob, j * 64, (j & ~1) * 72 + 64, bars + BAR_O * 8);
          if (atomicInc(&g_done, 127u) == 127u) atomicAdd(&g_epoch, 1u);
        }
      }
    }
  }
}

typedef CUresult (*EncodeFn)(CUtensorMap*, CUtensorMapDataType, cuuint32_t, void*, const cuuint64_t*, const cuuint64_t*, const cuuint32_t*,
                             const cuuint32_t*, CUtensorMapInterleave, CUtensorMapSwizzle, CUtensorMapL2promotion, CUtensorMapFloatOOBfill);

void encode2(EncodeFn fn, CUtensorMap* m, const void* p, uint64_t cols, uint64_t rows, uint32_t bc, uint32_t br, bool raw = false) {
  const cuuint64_t d[2] = {cols, rows}, s[1] = {cols * (raw ? 8 : 2)};
  const cuuint32_t b[2] = {bc, br}, es[2] = {1, 1};
  fn(m, raw ? CU_TENSOR_MAP_DATA_TYPE_UINT64 : CU_TENSOR_MAP_DATA_TYPE_BFLOAT16, 2, const_cast<void*>(p), d, s, b, es, CU_TENSOR_MAP_INTERLEAVE_NONE,
     raw ? CU_TENSOR_MAP_SWIZZLE_NONE : CU_TENSOR_MAP_SWIZZLE_128B, CU_TENSOR_MAP_L2_PROMOTION_L2_128B, CU_TENSOR_MAP_FLOAT_OOB_FILL_NONE);
}

}

extern "C" void kernel_launch(void* const* d_in, const int* in_sizes, int n_in, void* d_out, int out_size) {
  void* fp = nullptr;
  cudaDriverEntryPointQueryResult qr;
  cudaGetDriverEntryPoint("cuTensorMapEncodeTiled", &fp, cudaEnableDefault, &qr);
  EncodeFn fn = (EncodeFn)fp;
  void *qkv = nullptr, *op = nullptr;
  cudaGetSymbolAddress(&qkv, g_qkv);
  cudaGetSymbolAddress(&op, g_o);
  Maps mp;
  encode2(fn, &mp.x, d_in[0], DM, SEQ, 64, 128);
  encode2(fn, &mp.wqkv, d_in[1], 3 * DM, DM, 64, 64);
  encode2(fn, &mp.w24, d_in[1], 3 * DM, DM, 24, 64);
  encode2(fn, &mp.wg, d_in[4], FF, DM, 64, 64);
  encode2(fn, &mp.wu, d_in[5], FF, DM, 64, 64);
  encode2(fn, &mp.wd, d_in[6], DM, FF, 64, 64);
  encode2(fn, &mp.woa, d_in[2], DM, DM, 64, 64);
  encode2(fn, &mp.wob, d_in[2], DM, DM, 64, 16);
  encode2(fn, &mp.out, d_out, DM, SEQ, 64, 16);
  encode2(fn, &mp.lkv, qkv, 2 * SEQ, 216, 124, 9, true);
  encode2(fn, &mp.lq, qkv, 2 * SEQ, 216, 100, 9, true);
  encode2(fn, &mp.op, op, 18, 128 * 128, 2, 128, true);
  cudaFuncSetAttribute(fused_kernel, cudaFuncAttributeMaxDynamicSharedMemorySize, SMEM_BYTES);
  fused_kernel<<<128, 384, SMEM_BYTES, cudaStreamPerThread>>>(0u, mp);
}
```
